```python
import torch

def _softmax(x, axis=-1):
    return torch.softmax(x, dim=axis)

def _gelu(x):
    return torch.nn.functional.gelu(x, approximate='tanh')

def _silu(x):
    return torch.nn.functional.silu(x)

def _sigmoid(x):
    return torch.sigmoid(x)

def _layernorm(x, axis=-1, eps=1e-05):
    m = x.mean(dim=axis, keepdim=True)
    v = x.var(dim=axis, keepdim=True, unbiased=False)
    return (x - m) / torch.sqrt(v + eps)

def _scatter_add(tgt, idx, src, axis=0):
    return tgt.clone().index_add_(axis, idx, src)

def _segment_sum(src, seg, n):
    out = torch.zeros((n,) + src.shape[1:], dtype=src.dtype)
    return out.index_add_(0, seg, src)

def _pad(x, pw):
    flat = tuple((v for pair in reversed(pw) for v in pair))
    return torch.nn.functional.pad(x, flat)
kernel_name = 'gated_mix__memory_aug_recurrent_mem_tr__ssm_conv_s4__prompt'

def setup_inputs():

    _w = lambda a: (lambda t: t.to(torch.bfloat16) if t.is_floating_point() else t)(torch.as_tensor(a))

    def _A_setup():
        B, S, Dm = (1, 2048, 640)
        H, Dh = (32, 128)
        M, seg = (8, 32)
        seg = min(seg, S)
        S = S // seg * seg
        return {'x': _w((lambda *s: torch.randn(*s, dtype=torch.bfloat16) * 0.05)(B, S, Dm)), 'mem0': _w((lambda *s: torch.randn(*s, dtype=torch.bfloat16) * 0.4)(B, M, Dm)), 'Wq': _w((lambda *s: torch.randn(*s, dtype=torch.bfloat16) * 6.4)(Dm, H, Dh) * Dm ** (-0.5)), 'Wk': _w((lambda *s: torch.randn(*s, dtype=torch.bfloat16) * 6.4)(Dm, H, Dh) * Dm ** (-0.5)), 'Wv': _w((lambda *s: torch.randn(*s, dtype=torch.bfloat16) * 0.4)(Dm, H, Dh) * Dm ** (-0.5)), 'Wo': _w((lambda *s: torch.randn(*s, dtype=torch.bfloat16) * 0.4)(H, Dh, Dm) * (H * Dh) ** (-0.5)), 'seg_len': seg}
    _A_in = _A_setup()

    def _B_setup():
        B, L, D, N = (1, 2048, 640, 128)
        A_re = -(lambda _x: torch.exp(torch.as_tensor(_x)))((lambda *s: torch.randn(*s, dtype=torch.bfloat16) * 6.4)(D, N))
        A_im = torch.pi * (lambda *s: torch.randn(*s, dtype=torch.bfloat16) * 0.05)(D, N)
        B_re = (lambda *s: torch.randn(*s, dtype=torch.bfloat16) * 0.1)(D, N)
        B_im = (lambda *s: torch.randn(*s, dtype=torch.bfloat16) * 0.1)(D, N)
        C_re = (lambda *s: torch.randn(*s, dtype=torch.bfloat16) * 0.1)(D, N)
        C_im = (lambda *s: torch.randn(*s, dtype=torch.bfloat16) * 0.1)(D, N)
        log_dt = (lambda *s: torch.randn(*s, dtype=torch.bfloat16) * 0.05)(D) * 0.5 - 4.0
        Dskip = (lambda *s: torch.randn(*s, dtype=torch.bfloat16) * 0.05)(D)
        return {'u': _w((lambda *s: torch.randn(*s, dtype=torch.bfloat16) * 0.05)(B, L, D)), 'A_re': _w(A_re), 'A_im': _w(A_im), 'B_re': _w(B_re), 'B_im': _w(B_im), 'C_re': _w(C_re), 'C_im': _w(C_im), 'log_dt': _w(log_dt), 'Dskip': _w(Dskip)}
    _B_in = _B_setup()
    return {'A_x': _A_in['x'], 'A_mem0': _A_in['mem0'], 'A_Wq': _A_in['Wq'], 'A_Wk': _A_in['Wk'], 'A_Wv': _A_in['Wv'], 'A_Wo': _A_in['Wo'], 'A_seg_len': _A_in['seg_len'], 'B_u': _B_in['u'], 'B_A_re': _B_in['A_re'], 'B_A_im': _B_in['A_im'], 'B_B_re': _B_in['B_re'], 'B_B_im': _B_in['B_im'], 'B_C_re': _B_in['C_re'], 'B_C_im': _B_in['C_im'], 'B_log_dt': _B_in['log_dt'], 'B_Dskip': _B_in['Dskip'], 'gate_w': _w((lambda *s: torch.randn(*s, dtype=torch.bfloat16) * 0.05)(640) * 16.0)}

def reference(A_x, A_mem0, A_Wq, A_Wk, A_Wv, A_Wo, A_seg_len, B_u, B_A_re, B_A_im, B_B_re, B_B_im, B_C_re, B_C_im, B_log_dt, B_Dskip, gate_w):

    def _A_ref(x, mem0, Wq, Wk, Wv, Wo, seg_len):
        B, S, Dm = x.shape
        H, Dh = (Wq.shape[1], Wq.shape[2])
        M = mem0.shape[1]
        scale = Dh ** (-0.5)
        n_seg = S // seg_len
        L = M + seg_len
        idx = torch.arange(L)
        mask = (idx[:, None] < M) | (idx[:, None] >= idx[None, :])
        mem = mem0
        outs = []
        for s in range(n_seg):
            xs = x[:, s * seg_len:(s + 1) * seg_len, :].clone()
            h = torch.concatenate([mem, xs], axis=1)
            q = torch.einsum('btd,dhe->bhte', h, Wq)
            k = torch.einsum('btd,dhe->bhte', h, Wk)
            v = torch.einsum('btd,dhe->bhte', h, Wv)
            scores = torch.einsum('bhqe,bhke->bhqk', q, k) * scale
            scores = torch.where(mask[None, None], scores, -1000000000.0)
            p = _softmax(scores, axis=-1)
            o = torch.einsum('bhqk,bhke->bhqe', p, v)
            o = torch.einsum('bhte,hed->btd', o, Wo)
            mem = o[:, :M, :].clone()
            outs.append(o[:, M:, :])
        return torch.concatenate(outs, axis=1)

    def _B_ref(u, A_re, A_im, B_re, B_im, C_re, C_im, log_dt, Dskip):
        Bsz, L, D = u.shape
        dt = torch.exp(log_dt)[:, None]
        A = A_re + 1j * A_im
        Bc = B_re + 1j * B_im
        Cc = C_re + 1j * C_im
        logdA = dt * A
        dB = dt * Bc
        l = (lambda x, dt: x.to(dt))(torch.arange(L), A_re.dtype)
        P = torch.exp(logdA[:, :, None] * l[None, None, :])
        K = torch.einsum('dn,dnl,dn->dl', Cc, P, dB).real
        L2 = 2 * L
        Kp = _pad(K, ((0, 0), (0, L)))
        up = (lambda x, *d: x.permute(*d))(u, 0, 2, 1)
        up = _pad(up, ((0, 0), (0, 0), (0, L)))
        Kf = (lambda x, axes=(-2, -1): torch.fft.rfft2(x.float(), dim=axes))(Kp[:, None, :], axes=(-2, -1))
        Uf = (lambda x, axes=(-2, -1): torch.fft.rfft2(x.float(), dim=axes))(up[:, :, None, :], axes=(-2, -1))
        Yf = Uf * Kf[None, :, :, :]
        y = (lambda x, s, axes=(-2, -1): torch.fft.irfft2(x, s=s, dim=axes).to(torch.bfloat16))(Yf, (1, L2), axes=(-2, -1))[:, :, 0, :L]
        y = (lambda x, *d: x.permute(*d))(y, 0, 2, 1) + u * Dskip[None, None, :]
        return y
    x = A_x
    g = _sigmoid((x * gate_w).sum(-1, keepdims=True))
    a = _A_ref(x, A_mem0, A_Wq, A_Wk, A_Wv, A_Wo, A_seg_len)
    b = _B_ref(x, B_A_re, B_A_im, B_B_re, B_B_im, B_C_re, B_C_im, B_log_dt, B_Dskip)
    return g * a + (1 - g) * b
```

```cpp
__device__ bf16 g_qkv[(size_t)SEQ * 3 * HD];
__device__ bf16 g_o[(size_t)SEQ * HD];
__device__ bf16 g_km[NSEG * MTOK * HD];
__device__ bf16 g_vm[NSEG * MTOK * HD];
__device__ bf16 g_kbf[DM * SEQ];
__device__ bf16 g_bmix[SEQ * DM];
__device__ float g_gate[SEQ];
__device__ uint4 g_xbuf[2 * 4 * 16 * 80];
__device__ unsigned g_epoch;
__device__ unsigned g_mflags[64 * 64];
__device__ unsigned g_kvflags[16 * 48];
__device__ long long g_prof[64 * 1024];

template <typename T> static T* sym_addr(const T& sym) { void* p = nullptr; cudaGetSymbolAddress(&p, sym); return (T*)p; }

struct HostState {
  bool init;
  const void* in_key[17]; void* out_key;
  CUtensorMap tmWq128, tmWk128, tmWv128, tmWoC, tmKV32;
  CUtensorMap tmX, tmWqB, tmWkB, tmWvB, tmQKVst;
  CUtensorMap tmQKV64, tmKM, tmVM, tmOst;
  CUtensorMap tmOA, tmWoB;
  cudaStream_t s2; cudaEvent_t evFork, evJoin;
};
static HostState H;

template <typename K, typename... Args>
static void launch_ex(K k, dim3 grid, dim3 block, int smem, cudaStream_t st, int cluster, cudaEvent_t launch_done, Args... args) {
  cudaLaunchConfig_t cfg = {};
  cfg.gridDim = grid; cfg.blockDim = block; cfg.dynamicSmemBytes = smem; cfg.stream = st;
  cudaLaunchAttribute at[2]; int n = 0;
  if (cluster > 1) { at[n].id = cudaLaunchAttributeClusterDimension; at[n].val.clusterDim.x = cluster; at[n].val.clusterDim.y = 1; at[n].val.clusterDim.z = 1; n++; }
  if (launch_done) { at[n].id = cudaLaunchAttributeLaunchCompletionEvent; at[n].val.launchCompletionEvent.event = launch_done; at[n].val.launchCompletionEvent.flags = 0; n++; }
  cfg.attrs = at; cfg.numAttrs = n;
  cudaLaunchKernelEx(&cfg, k, args...);
}
#include <cstdio>
#include <string>

extern "C" void kernel_launch(void* const* d_in, const int* in_sizes, int n_in, void* d_out, int out_size);

#define MODE 0

extern "C" void kernel_launch(void* const* d_in, const int* in_sizes, int n_in, void* d_out, int out_size) {
  const bf16 *x = (const bf16*)d_in[0], *mem0 = (const bf16*)d_in[1], *Wq = (const bf16*)d_in[2], *Wk = (const bf16*)d_in[3],
             *Wv = (const bf16*)d_in[4], *Wo = (const bf16*)d_in[5];
  bool rebuild = !H.init;
  for (int i = 0; i < 17 && !rebuild; i++) if (H.in_key[i] != d_in[i]) rebuild = true;
  if (!rebuild && H.out_key != d_out) rebuild = true;
  bf16* qkv = sym_addr(g_qkv[0]); bf16* o = sym_addr(g_o[0]); bf16* km = sym_addr(g_km[0]); bf16* vm = sym_addr(g_vm[0]);
  if (rebuild) {
    for (int i = 0; i < 17; i++) H.in_key[i] = d_in[i];
    H.out_key = d_out;
    H.tmWq128 = make_tmap(Wq, 640, 4096, 128, 64); H.tmWk128 = make_tmap(Wk, 640, 4096, 128, 64); H.tmWv128 = make_tmap(Wv, 640, 4096, 128, 64);
    H.tmWoC = make_tmap(Wo, 4096, 640, 128, 64); H.tmKV32 = make_tmap(qkv, 2048, 12288, 32, 64);
    H.tmX = make_tmap(x, 2048, 640, 128, 64);
    H.tmWqB = make_tmap(Wq, 640, 4096, 64, 64); H.tmWkB = make_tmap(Wk, 640, 4096, 64, 64); H.tmWvB = make_tmap(Wv, 640, 4096, 64, 64);
    H.tmQKVst = make_tmap(qkv, 2048, 12288, 64, 64); H.tmQKV64 = H.tmQKVst;
    H.tmKM = make_tmap(km, 512, 4096, 16, 64); H.tmVM = make_tmap(vm, 512, 4096, 16, 64);
    H.tmOst = make_tmap(o, 2048, 4096, 64, 64);
    H.tmOA = make_tmap(o, 2048, 4096, 128, 64); H.tmWoB = make_tmap(Wo, 4096, 640, 64, 64);
    if (!H.init) {
      cudaFuncSetAttribute(chain_kernel, cudaFuncAttributeMaxDynamicSharedMemorySize, chain::SMEM_BYTES);
      cudaFuncSetAttribute(chain_kernel, cudaFuncAttributeNonPortableClusterSizeAllowed, 1);
      cudaFuncSetAttribute(gemm_kernel<256, 0>, cudaFuncAttributeMaxDynamicSharedMemorySize, gemm::Cfg<256>::SMEM);
      cudaFuncSetAttribute(gemm_kernel<128, 1>, cudaFuncAttributeMaxDynamicSharedMemorySize, gemm::Cfg<128>::SMEM);
      cudaFuncSetAttribute(attn_kernel, cudaFuncAttributeMaxDynamicSharedMemorySize, attn::SMEM);
      cudaFuncSetAttribute(conv_kernel, cudaFuncAttributeMaxDynamicSharedMemorySize, conv::SMEM);
      cudaStreamCreateWithFlags(&H.s2, cudaStreamNonBlocking);
      cudaEventCreateWithFlags(&H.evFork, cudaEventDisableTiming);
      cudaEventCreateWithFlags(&H.evJoin, cudaEventDisableTiming);
    }
    H.init = true;
  }
  cudaStream_t s1 = cudaStreamPerThread;
  ChainParams cp;
  cp.mem0 = mem0; cp.km = km; cp.vm = vm; cp.xbuf = sym_addr(g_xbuf[0]); cp.epoch = sym_addr(g_epoch); cp.kv_flags = sym_addr(g_kvflags[0]);
  cp.m_flags = sym_addr(g_mflags[0]); cp.prof = sym_addr(g_prof[0]);
  GemmParams g1 = {}; g1.tile_begin = 0; g1.tile_end = 768; g1.kblocks = 10; g1.flags = cp.kv_flags;
  SsmParams sp;
  sp.A_re = (const bf16*)d_in[8]; sp.A_im = (const bf16*)d_in[9]; sp.B_re = (const bf16*)d_in[10]; sp.B_im = (const bf16*)d_in[11];
  sp.C_re = (const bf16*)d_in[12]; sp.C_im = (const bf16*)d_in[13]; sp.log_dt = (const bf16*)d_in[14]; sp.Dskip = (const bf16*)d_in[15];
  sp.x = x; sp.gate_w = (const bf16*)d_in[16]; sp.kbf = sym_addr(g_kbf[0]); sp.gate = sym_addr(g_gate[0]); sp.bmix = sym_addr(g_bmix[0]);
  AttnParams ap; ap.rt_begin = 0; ap.m_flags = cp.m_flags; ap.epoch = cp.epoch;
  GemmParams g2 = {}; g2.tile_begin = 0; g2.tile_end = 80; g2.kblocks = 64; g2.gate = sp.gate; g2.bmix = sp.bmix; g2.out = (bf16*)d_out;
  g2.epoch = cp.epoch; g2.bump_epoch = 1;

  launch_ex(gemm_kernel<256, 0>, dim3(132), dim3(288), gemm::Cfg<256>::SMEM, s1, 1, nullptr, H.tmX, H.tmWqB, H.tmWkB, H.tmWvB, H.tmQKVst, g1);
  launch_ex(ssm_gen_kernel, dim3(640 + 256), dim3(256), 0, s1, 1, nullptr, sp);
  launch_ex(conv_kernel, dim3(160), dim3(128), conv::SMEM, s1, 1, nullptr, sp);
  launch_ex(chain_kernel, dim3(64), dim3(256), chain::SMEM_BYTES, s1, 16, nullptr, H.tmWq128, H.tmWk128, H.tmWv128, H.tmWoC, H.tmKV32, cp);
  launch_ex(attn_kernel, dim3(1024), dim3(128), attn::SMEM, s1, 1, nullptr, H.tmQKV64, H.tmKM, H.tmVM, H.tmOst, ap);
  launch_ex(gemm_kernel<128, 1>, dim3(80), dim3(288), gemm::Cfg<128>::SMEM, s1, 1, nullptr, H.tmOA, H.tmWoB, H.tmWoB, H.tmWoB, H.tmOst, g2);
}
```

```cpp
__device__ bf16 g_qkv[(size_t)SEQ * 3 * HD];
__device__ bf16 g_o[(size_t)SEQ * HD];
__device__ bf16 g_km[NSEG * MTOK * HD];
__device__ bf16 g_vm[NSEG * MTOK * HD];
__device__ bf16 g_kbf[DM * SEQ];
__device__ bf16 g_bmix[SEQ * DM];
__device__ float g_gate[SEQ];
__device__ uint4 g_xbuf[2 * 4 * 16 * 80];
__device__ unsigned g_epoch;
__device__ unsigned g_mflags[64 * 64];
__device__ unsigned g_kvflags[16 * 48];
__device__ long long g_prof[64 * 1024];

template <typename T> static T* sym_addr(const T& sym) { void* p = nullptr; cudaGetSymbolAddress(&p, sym); return (T*)p; }

struct HostState {
  bool init;
  const void* in_key[17]; void* out_key;
  CUtensorMap tmWq128, tmWk128, tmWv128, tmWoC, tmKV32;
  CUtensorMap tmX, tmWqB, tmWkB, tmWvB, tmQKVst;
  CUtensorMap tmQKV64, tmKM, tmVM, tmOst;
  CUtensorMap tmOA, tmWoB;
  cudaStream_t s2; cudaEvent_t evFork, evJoin;
  int nsm;
};
static HostState H;

template <typename K, typename... Args>
static void launch_ex(K k, dim3 grid, dim3 block, int smem, cudaStream_t st, int cluster, cudaEvent_t launch_done, Args... args) {
  cudaLaunchConfig_t cfg = {};
  cfg.gridDim = grid; cfg.blockDim = block; cfg.dynamicSmemBytes = smem; cfg.stream = st;
  cudaLaunchAttribute at[2]; int n = 0;
  if (cluster > 1) { at[n].id = cudaLaunchAttributeClusterDimension; at[n].val.clusterDim.x = cluster; at[n].val.clusterDim.y = 1; at[n].val.clusterDim.z = 1; n++; }
  if (launch_done) { at[n].id = cudaLaunchAttributeLaunchCompletionEvent; at[n].val.launchCompletionEvent.event = launch_done; at[n].val.launchCompletionEvent.flags = 0; n++; }
  cfg.attrs = at; cfg.numAttrs = n;
  cudaLaunchKernelEx(&cfg, k, args...);
}
#include <cstdio>
#include <string>

extern "C" void kernel_launch(void* const* d_in, const int* in_sizes, int n_in, void* d_out, int out_size);

#define MODE 1

extern "C" void kernel_launch(void* const* d_in, const int* in_sizes, int n_in, void* d_out, int out_size) {
  const bf16 *x = (const bf16*)d_in[0], *mem0 = (const bf16*)d_in[1], *Wq = (const bf16*)d_in[2], *Wk = (const bf16*)d_in[3],
             *Wv = (const bf16*)d_in[4], *Wo = (const bf16*)d_in[5];
  bool rebuild = !H.init;
  for (int i = 0; i < 17 && !rebuild; i++) if (H.in_key[i] != d_in[i]) rebuild = true;
  if (!rebuild && H.out_key != d_out) rebuild = true;
  bf16* qkv = sym_addr(g_qkv[0]); bf16* o = sym_addr(g_o[0]); bf16* km = sym_addr(g_km[0]); bf16* vm = sym_addr(g_vm[0]);
  if (rebuild) {
    for (int i = 0; i < 17; i++) H.in_key[i] = d_in[i];
    H.out_key = d_out;
    H.tmWq128 = make_tmap(Wq, 640, 4096, 128, 64); H.tmWk128 = make_tmap(Wk, 640, 4096, 128, 64); H.tmWv128 = make_tmap(Wv, 640, 4096, 128, 64);
    H.tmWoC = make_tmap(Wo, 4096, 640, 128, 64); H.tmKV32 = make_tmap(qkv, 2048, 12288, 32, 64);
    H.tmX = make_tmap(x, 2048, 640, 128, 64);
    H.tmWqB = make_tmap(Wq, 640, 4096, 64, 64); H.tmWkB = make_tmap(Wk, 640, 4096, 64, 64); H.tmWvB = make_tmap(Wv, 640, 4096, 64, 64);
    H.tmQKVst = make_tmap(qkv, 2048, 12288, 64, 64); H.tmQKV64 = H.tmQKVst;
    H.tmKM = make_tmap(km, 512, 4096, 16, 64); H.tmVM = make_tmap(vm, 512, 4096, 16, 64);
    H.tmOst = make_tmap(o, 2048, 4096, 64, 64);
    H.tmOA = make_tmap(o, 2048, 4096, 128, 64); H.tmWoB = make_tmap(Wo, 4096, 640, 64, 64);
    if (!H.init) {
      cudaFuncSetAttribute(chain_kernel, cudaFuncAttributeMaxDynamicSharedMemorySize, chain::SMEM_BYTES);
      cudaFuncSetAttribute(chain_kernel, cudaFuncAttributeNonPortableClusterSizeAllowed, 1);
      cudaFuncSetAttribute(gemm_kernel<256, 0>, cudaFuncAttributeMaxDynamicSharedMemorySize, gemm::Cfg<256>::SMEM);
      cudaFuncSetAttribute(gemm_kernel<128, 1>, cudaFuncAttributeMaxDynamicSharedMemorySize, gemm::Cfg<128>::SMEM);
      cudaFuncSetAttribute(out_kernel, cudaFuncAttributeMaxDynamicSharedMemorySize, outp::SMEM);
      cudaDeviceGetAttribute(&H.nsm, cudaDevAttrMultiProcessorCount, 0);
      cudaFuncSetAttribute(attn_kernel, cudaFuncAttributeMaxDynamicSharedMemorySize, attn::SMEM);
      cudaFuncSetAttribute(conv_kernel, cudaFuncAttributeMaxDynamicSharedMemorySize, conv::SMEM);
      cudaStreamCreateWithFlags(&H.s2, cudaStreamNonBlocking);
      cudaEventCreateWithFlags(&H.evFork, cudaEventDisableTiming);
      cudaEventCreateWithFlags(&H.evJoin, cudaEventDisableTiming);
    }
    H.init = true;
  }
  cudaStream_t s1 = cudaStreamPerThread;
  ChainParams cp;
  cp.mem0 = mem0; cp.km = km; cp.vm = vm; cp.xbuf = sym_addr(g_xbuf[0]); cp.epoch = sym_addr(g_epoch); cp.kv_flags = sym_addr(g_kvflags[0]);
  cp.m_flags = sym_addr(g_mflags[0]); cp.prof = sym_addr(g_prof[0]);
  GemmParams g1 = {}; g1.tile_begin = 0; g1.tile_end = 768; g1.kblocks = 10; g1.flags = cp.kv_flags;
  SsmParams sp;
  sp.A_re = (const bf16*)d_in[8]; sp.A_im = (const bf16*)d_in[9]; sp.B_re = (const bf16*)d_in[10]; sp.B_im = (const bf16*)d_in[11];
  sp.C_re = (const bf16*)d_in[12]; sp.C_im = (const bf16*)d_in[13]; sp.log_dt = (const bf16*)d_in[14]; sp.Dskip = (const bf16*)d_in[15];
  sp.x = x; sp.gate_w = (const bf16*)d_in[16]; sp.kbf = sym_addr(g_kbf[0]); sp.gate = sym_addr(g_gate[0]); sp.bmix = sym_addr(g_bmix[0]);
  AttnParams ap; ap.rt_begin = 0; ap.m_flags = cp.m_flags; ap.epoch = cp.epoch;
  GemmParams g2 = {}; g2.tile_begin = 0; g2.tile_end = 80; g2.kblocks = 64; g2.gate = sp.gate; g2.bmix = sp.bmix; g2.out = (bf16*)d_out;
  g2.epoch = cp.epoch; g2.bump_epoch = 1;

  cudaStream_t s2 = H.s2;
  launch_ex(chain_kernel, dim3(64), dim3(256), chain::SMEM_BYTES, s1, 16, H.evFork, H.tmWq128, H.tmWk128, H.tmWv128, H.tmWoC, H.tmKV32, cp);
  cudaStreamWaitEvent(s2, H.evFork, 0);
  const int nfree = H.nsm - 64;
  launch_ex(gemm_kernel<256, 0>, dim3(nfree), dim3(288), gemm::Cfg<256>::SMEM, s2, 1, nullptr, H.tmX, H.tmWqB, H.tmWkB, H.tmWvB, H.tmQKVst, g1);
  launch_ex(ssm_gen_kernel, dim3(640 + 256), dim3(256), 0, s2, 1, nullptr, sp);
  launch_ex(conv_kernel, dim3(160), dim3(128), conv::SMEM, s2, 1, nullptr, sp);
  {
    const int bounds[] = {0, 6, 10, 13, 15, 16};
    const int nch = sizeof(bounds) / sizeof(int) - 1;
    for (int c = 0; c < nch; c++) {
      const int r0 = bounds[c], r1 = bounds[c + 1];
      ap.rt_begin = 2 * r0;
      launch_ex(attn_kernel, dim3(64 * (r1 - r0)), dim3(128), attn::SMEM, s2, 1, nullptr, H.tmQKV64, H.tmKM, H.tmVM, H.tmOst, ap);
      OutParams op; op.rt_begin = r0; op.gate = sp.gate; op.bmix = sp.bmix; op.out = (bf16*)d_out; op.epoch = cp.epoch; op.bump_epoch = (c == nch - 1);
      launch_ex(out_kernel, dim3(5 * (r1 - r0) * outp::KS), dim3(288), outp::SMEM, s2, outp::KS, nullptr, H.tmOA, H.tmWoB, op);
    }
  }
  cudaEventRecord(H.evJoin, s2);
  cudaStreamWaitEvent(s1, H.evJoin, 0);
}
```

```cpp
__device__ bf16 g_qkv[(size_t)SEQ * 3 * HD];
__device__ bf16 g_o[(size_t)SEQ * HD];
__device__ bf16 g_km[NSEG * MTOK * HD];
__device__ bf16 g_vm[NSEG * MTOK * HD];
__device__ __align__(128) bf16 g_kbf[DM * 2 * 2080];
__device__ __align__(128) bf16 g_xT[DM * 2176];
__device__ bf16 g_bmix[SEQ * DM];
__device__ float g_gate[SEQ];
__device__ uint4 g_xbuf[2 * 4 * 16 * 80];
__device__ unsigned g_epoch;
__device__ unsigned g_mflags[64 * 64];
__device__ unsigned g_kvflags[16 * 48];
__device__ long long g_prof[64 * 1024];

template <typename T> static T* sym_addr(const T& sym) { void* p = nullptr; cudaGetSymbolAddress(&p, sym); return (T*)p; }

struct HostState {
  bool init;
  const void* in_key[17]; void* out_key;
  CUtensorMap tmWq128, tmWk128, tmWv128, tmWoC, tmKV32;
  CUtensorMap tmX, tmWqB, tmWkB, tmWvB, tmQKVst;
  CUtensorMap tmQKV64, tmKM, tmVM, tmOst;
  CUtensorMap tmOA, tmWoB;
  cudaStream_t s2, s3, s4; cudaEvent_t evFork, evJoin, evQ, evSsm, evA[8], evO[8]; cudaStream_t so[8];
  int nsm;
};
static HostState H;

template <typename K, typename... Args>
static void launch_ex(K k, dim3 grid, dim3 block, int smem, cudaStream_t st, int cluster, cudaEvent_t launch_done, Args... args) {
  cudaLaunchConfig_t cfg = {};
  cfg.gridDim = grid; cfg.blockDim = block; cfg.dynamicSmemBytes = smem; cfg.stream = st;
  cudaLaunchAttribute at[2]; int n = 0;
  if (cluster > 1) { at[n].id = cudaLaunchAttributeClusterDimension; at[n].val.clusterDim.x = cluster; at[n].val.clusterDim.y = 1; at[n].val.clusterDim.z = 1; n++; }
  if (launch_done) { at[n].id = cudaLaunchAttributeLaunchCompletionEvent; at[n].val.launchCompletionEvent.event = launch_done; at[n].val.launchCompletionEvent.flags = 0; n++; }
  cfg.attrs = at; cfg.numAttrs = n;
  cudaLaunchKernelEx(&cfg, k, args...);
}
#include <cstdio>
#include <string>

extern "C" void kernel_launch(void* const* d_in, const int* in_sizes, int n_in, void* d_out, int out_size);

#define CHUNKS {0, 4, 8, 11, 13, 15, 16}
#define NSPLIT 2
#define MODE 1

extern "C" void kernel_launch(void* const* d_in, const int* in_sizes, int n_in, void* d_out, int out_size) {
  const bf16 *x = (const bf16*)d_in[0], *mem0 = (const bf16*)d_in[1], *Wq = (const bf16*)d_in[2], *Wk = (const bf16*)d_in[3],
             *Wv = (const bf16*)d_in[4], *Wo = (const bf16*)d_in[5];
  bool rebuild = !H.init;
  for (int i = 0; i < 17 && !rebuild; i++) if (H.in_key[i] != d_in[i]) rebuild = true;
  if (!rebuild && H.out_key != d_out) rebuild = true;
  bf16* qkv = sym_addr(g_qkv[0]); bf16* o = sym_addr(g_o[0]); bf16* km = sym_addr(g_km[0]); bf16* vm = sym_addr(g_vm[0]);
  if (rebuild) {
    for (int i = 0; i < 17; i++) H.in_key[i] = d_in[i];
    H.out_key = d_out;
    H.tmWq128 = make_tmap(Wq, 640, 4096, 128, 64); H.tmWk128 = make_tmap(Wk, 640, 4096, 128, 64); H.tmWv128 = make_tmap(Wv, 640, 4096, 128, 64);
    H.tmWoC = make_tmap(Wo, 4096, 640, 128, 64); H.tmKV32 = make_tmap(qkv, 2048, 12288, 32, 64);
    H.tmX = make_tmap(x, 2048, 640, 128, 64);
    H.tmWqB = make_tmap(Wq, 640, 4096, 64, 64); H.tmWkB = make_tmap(Wk, 640, 4096, 64, 64); H.tmWvB = make_tmap(Wv, 640, 4096, 64, 64);
    H.tmQKVst = make_tmap(qkv, 2048, 12288, 64, 64); H.tmQKV64 = H.tmQKVst;
    H.tmKM = make_tmap(km, 512, 4096, 16, 64); H.tmVM = make_tmap(vm, 512, 4096, 16, 64);
    H.tmOst = make_tmap(o, 2048, 4096, 64, 64);
    H.tmOA = make_tmap(o, 2048, 4096, 128, 64); H.tmWoB = make_tmap(Wo, 4096, 640, 64, 64);
    if (!H.init) {
      cudaFuncSetAttribute(chain_kernel, cudaFuncAttributeMaxDynamicSharedMemorySize, chain::SMEM_BYTES);
      cudaFuncSetAttribute(chain_kernel, cudaFuncAttributeNonPortableClusterSizeAllowed, 1);
      cudaFuncSetAttribute(gemm_kernel<256, 0, 2>, cudaFuncAttributeMaxDynamicSharedMemorySize, gemm::Cfg<256>::SMEM);
      cudaFuncSetAttribute(gemm_kernel<128, 1, 1>, cudaFuncAttributeMaxDynamicSharedMemorySize, gemm::Cfg<128>::SMEM);
      cudaFuncSetAttribute(out_kernel, cudaFuncAttributeMaxDynamicSharedMemorySize, outp::SMEM);
      cudaDeviceGetAttribute(&H.nsm, cudaDevAttrMultiProcessorCount, 0);
      cudaFuncSetAttribute(attn_kernel, cudaFuncAttributeMaxDynamicSharedMemorySize, attn::SMEM);
      cudaFuncSetAttribute(conv_kernel, cudaFuncAttributeMaxDynamicSharedMemorySize, conv::SMEM);
      cudaStreamCreateWithFlags(&H.s2, cudaStreamNonBlocking);
      cudaStreamCreateWithFlags(&H.s3, cudaStreamNonBlocking); cudaStreamCreateWithFlags(&H.s4, cudaStreamNonBlocking);
      cudaEventCreateWithFlags(&H.evQ, cudaEventDisableTiming); cudaEventCreateWithFlags(&H.evSsm, cudaEventDisableTiming);
      for (int i = 0; i < 8; i++) { cudaEventCreateWithFlags(&H.evA[i], cudaEventDisableTiming); cudaEventCreateWithFlags(&H.evO[i], cudaEventDisableTiming); cudaStreamCreateWithFlags(&H.so[i], cudaStreamNonBlocking); }
      cudaEventCreateWithFlags(&H.evFork, cudaEventDisableTiming);
      cudaEventCreateWithFlags(&H.evJoin, cudaEventDisableTiming);
    }
    H.init = true;
  }
  cudaStream_t s1 = cudaStreamPerThread;
  ChainParams cp;
  cp.mem0 = mem0; cp.km = km; cp.vm = vm; cp.xbuf = sym_addr(g_xbuf[0]); cp.epoch = sym_addr(g_epoch); cp.kv_flags = sym_addr(g_kvflags[0]);
  cp.m_flags = sym_addr(g_mflags[0]); cp.prof = sym_addr(g_prof[0]);
  GemmParams g1 = {}; g1.tile_begin = 0; g1.tile_end = 384; g1.kblocks = 10; g1.flags = cp.kv_flags;
  SsmParams sp;
  sp.A_re = (const bf16*)d_in[8]; sp.A_im = (const bf16*)d_in[9]; sp.B_re = (const bf16*)d_in[10]; sp.B_im = (const bf16*)d_in[11];
  sp.C_re = (const bf16*)d_in[12]; sp.C_im = (const bf16*)d_in[13]; sp.log_dt = (const bf16*)d_in[14]; sp.Dskip = (const bf16*)d_in[15];
  sp.x = x; sp.gate_w = (const bf16*)d_in[16]; sp.kbf = sym_addr(g_kbf[0]); sp.xT = sym_addr(g_xT[0]); sp.gate = sym_addr(g_gate[0]); sp.bmix = sym_addr(g_bmix[0]);
  AttnParams ap; ap.kid = 0; ap.rt_begin = 0; ap.m_flags = cp.m_flags; ap.epoch = cp.epoch;
  GemmParams g2 = {}; g2.tile_begin = 0; g2.tile_end = 80; g2.kblocks = 64; g2.gate = sp.gate; g2.bmix = sp.bmix; g2.out = (bf16*)d_out;
  g2.epoch = cp.epoch; g2.bump_epoch = 1;

  cudaStream_t s2 = H.s2, s4 = H.s4;
  launch_ex(chain_kernel, dim3(64), dim3(256), chain::SMEM_BYTES, s1, 16, H.evFork, H.tmWq128, H.tmWk128, H.tmWv128, H.tmWoC, H.tmKV32, cp);
  cudaStreamWaitEvent(s2, H.evFork, 0);
  const int nfree = H.nsm - 64;
  launch_ex(gemm_kernel<256, 0, 2>, dim3(nfree & ~1), dim3(320), gemm::Cfg<256>::SMEM, s2, 2, H.evQ, H.tmX, H.tmWqB, H.tmWkB, H.tmWvB, H.tmQKVst, g1);
  cudaStreamWaitEvent(s4, H.evQ, 0);
  launch_ex(ssm_gen_kernel, dim3(640 + 64), dim3(256), 0, s4, 1, nullptr, sp);
  launch_ex(conv_kernel, dim3(160), dim3(128), conv::SMEM, s4, 1, nullptr, sp);
  cudaEventRecord(H.evSsm, s4);
  {
    const int bounds[] = CHUNKS;
    const int nch = sizeof(bounds) / sizeof(int) - 1;
    for (int c = 0; c < nch; c++) {
      const int r0 = bounds[c], r1 = bounds[c + 1];
      const bool lastc = (c == nch - 1);
      ap.rt_begin = 2 * r0; ap.kid = 2 * c;
      if (!lastc) launch_ex(gate_kernel, dim3(1), dim3(64), 0, s2, 1, nullptr, (const unsigned*)cp.m_flags, (const unsigned*)cp.epoch, 4 * r1 - 1);
      launch_ex(attn_kernel, dim3(64 * (r1 - r0)), dim3(128), attn::SMEM, s2, 1, nullptr, H.tmQKV64, H.tmKM, H.tmVM, H.tmOst, ap);
      cudaEventRecord(H.evA[c], s2);
      cudaStream_t so = H.so[c];
      cudaStreamWaitEvent(so, H.evA[c], 0);
      cudaStreamWaitEvent(so, H.evSsm, 0);
      if (c < nch - NSPLIT) {
        GemmParams gp = g2; gp.tile_begin = 5 * r0; gp.tile_end = 5 * r1; gp.bump_epoch = 0; gp.kid = 2 * c;
        launch_ex(gemm_kernel<128, 1, 1>, dim3(5 * (r1 - r0)), dim3(320), gemm::Cfg<128>::SMEM, so, 1, nullptr, H.tmOA, H.tmWoB, H.tmWoB, H.tmWoB, H.tmOst, gp);
      } else {
        OutParams op; op.rt_begin = r0; op.gate = sp.gate; op.bmix = sp.bmix; op.out = (bf16*)d_out; op.epoch = cp.epoch; op.bump_epoch = lastc; op.kid = 2 * c;
        launch_ex(out_kernel, dim3(5 * (r1 - r0) * outp::KS), dim3(288), outp::SMEM, so, outp::KS, nullptr, H.tmOA, H.tmWoB, op);
      }
      cudaEventRecord(H.evO[c], so);
      cudaStreamWaitEvent(s1, H.evO[c], 0);
    }
  }
}
```

```cpp
__device__ bf16 g_qkv[(size_t)SEQ * 3 * HD];
__device__ bf16 g_o[(size_t)SEQ * HD];
__device__ bf16 g_km[NSEG * MTOK * HD];
__device__ bf16 g_vm[NSEG * MTOK * HD];
__device__ __align__(128) bf16 g_kbf[DM * 2 * 2080];
__device__ __align__(128) bf16 g_xT[DM * 2176];
__device__ bf16 g_bmix[SEQ * DM];
__device__ float g_gate[SEQ];
__device__ uint4 g_xbuf[2 * 4 * 16 * 80];
__device__ unsigned g_epoch[2];
__device__ unsigned g_oflags[32];
__device__ unsigned g_mflags[64 * 64];
__device__ unsigned g_kvflags[16 * 64];
__device__ long long g_prof[64 * 1024];

template <typename T> static T* sym_addr(const T& sym) { void* p = nullptr; cudaGetSymbolAddress(&p, sym); return (T*)p; }

struct HostState {
  bool init;
  const void* in_key[17]; void* out_key;
  CUtensorMap tmWq128, tmWk128, tmWv128, tmWoC, tmKV32;
  CUtensorMap tmX, tmWqB, tmWkB, tmWvB, tmQKVst;
  CUtensorMap tmQKV64, tmKM, tmVM, tmOst;
  CUtensorMap tmOA, tmWoB;
  cudaStream_t s2, s3, s4; cudaEvent_t evFork, evJoin, evQ, evQ0, evQ0done, evL, evSsm, evA[8], evO[8]; cudaStream_t so[8];
  int nsm;
};
static HostState H;

template <typename K, typename... Args>
static void launch_ex(K k, dim3 grid, dim3 block, int smem, cudaStream_t st, int cluster, cudaEvent_t launch_done, Args... args) {
  cudaLaunchConfig_t cfg = {};
  cfg.gridDim = grid; cfg.blockDim = block; cfg.dynamicSmemBytes = smem; cfg.stream = st;
  cudaLaunchAttribute at[2]; int n = 0;
  if (cluster > 1) { at[n].id = cudaLaunchAttributeClusterDimension; at[n].val.clusterDim.x = cluster; at[n].val.clusterDim.y = 1; at[n].val.clusterDim.z = 1; n++; }
  if (launch_done) { at[n].id = cudaLaunchAttributeLaunchCompletionEvent; at[n].val.launchCompletionEvent.event = launch_done; at[n].val.launchCompletionEvent.flags = 0; n++; }
  cfg.attrs = at; cfg.numAttrs = n;
  cudaLaunchKernelEx(&cfg, k, args...);
}
#include <cstdio>
#include <string>

extern "C" void kernel_launch(void* const* d_in, const int* in_sizes, int n_in, void* d_out, int out_size);

#define CHUNKS {0, 4, 8, 11, 13, 14, 15, 16}
#define NSPLIT 3
#define LAST_KS 4
#define MODE 1

extern "C" void kernel_launch(void* const* d_in, const int* in_sizes, int n_in, void* d_out, int out_size) {
  const bf16 *x = (const bf16*)d_in[0], *mem0 = (const bf16*)d_in[1], *Wq = (const bf16*)d_in[2], *Wk = (const bf16*)d_in[3],
             *Wv = (const bf16*)d_in[4], *Wo = (const bf16*)d_in[5];
  bool rebuild = !H.init;
  for (int i = 0; i < 17 && !rebuild; i++) if (H.in_key[i] != d_in[i]) rebuild = true;
  if (!rebuild && H.out_key != d_out) rebuild = true;
  bf16* qkv = sym_addr(g_qkv[0]); bf16* o = sym_addr(g_o[0]); bf16* km = sym_addr(g_km[0]); bf16* vm = sym_addr(g_vm[0]);
  if (rebuild) {
    for (int i = 0; i < 17; i++) H.in_key[i] = d_in[i];
    H.out_key = d_out;
    H.tmWq128 = make_tmap(Wq, 640, 4096, 128, 64); H.tmWk128 = make_tmap(Wk, 640, 4096, 128, 64); H.tmWv128 = make_tmap(Wv, 640, 4096, 128, 64);
    H.tmWoC = make_tmap(Wo, 4096, 640, 128, 64); H.tmKV32 = make_tmap(qkv, 2048, 12288, 32, 64);
    H.tmX = make_tmap(x, 2048, 640, 128, 64);
    H.tmWqB = make_tmap(Wq, 640, 4096, 64, 64); H.tmWkB = make_tmap(Wk, 640, 4096, 64, 64); H.tmWvB = make_tmap(Wv, 640, 4096, 64, 64);
    H.tmQKVst = make_tmap(qkv, 2048, 12288, 64, 64); H.tmQKV64 = H.tmQKVst;
    H.tmKM = make_tmap(km, 512, 4096, 16, 64); H.tmVM = make_tmap(vm, 512, 4096, 16, 64);
    H.tmOst = make_tmap(o, 2048, 4096, 64, 64);
    H.tmOA = make_tmap(o, 2048, 4096, 128, 64); H.tmWoB = make_tmap(Wo, 4096, 640, 64, 64);
    if (!H.init) {
      cudaFuncSetAttribute(chain_kernel, cudaFuncAttributeMaxDynamicSharedMemorySize, chain::SMEM_BYTES);
      cudaFuncSetAttribute(chain_kernel, cudaFuncAttributeNonPortableClusterSizeAllowed, 1);
      cudaFuncSetAttribute(gemm_kernel<128, 1, 1>, cudaFuncAttributeMaxDynamicSharedMemorySize, gemm::Cfg<128>::SMEM);
      cudaFuncSetAttribute(gemm_kernel<256, 0, 2>, cudaFuncAttributeMaxDynamicSharedMemorySize, gemm::Cfg<256>::SMEM);
      cudaFuncSetAttribute(gemm_kernel<128, 0, 1>, cudaFuncAttributeMaxDynamicSharedMemorySize, gemm::Cfg<128>::SMEM);
      cudaEventCreateWithFlags(&H.evQ0, cudaEventDisableTiming); cudaEventCreateWithFlags(&H.evQ0done, cudaEventDisableTiming);
      cudaFuncSetAttribute(out_kernel<4>, cudaFuncAttributeMaxDynamicSharedMemorySize, outp::Cfg<4>::SMEM);
      cudaFuncSetAttribute(out_kernel<8>, cudaFuncAttributeMaxDynamicSharedMemorySize, outp::Cfg<8>::SMEM);
      cudaEventCreateWithFlags(&H.evL, cudaEventDisableTiming);
      cudaDeviceGetAttribute(&H.nsm, cudaDevAttrMultiProcessorCount, 0);
      cudaFuncSetAttribute(attn_kernel, cudaFuncAttributeMaxDynamicSharedMemorySize, attn::SMEM);
      cudaFuncSetAttribute(conv_kernel, cudaFuncAttributeMaxDynamicSharedMemorySize, conv::SMEM);
      cudaStreamCreateWithFlags(&H.s2, cudaStreamNonBlocking);
      cudaStreamCreateWithFlags(&H.s3, cudaStreamNonBlocking); cudaStreamCreateWithFlags(&H.s4, cudaStreamNonBlocking);
      cudaEventCreateWithFlags(&H.evQ, cudaEventDisableTiming); cudaEventCreateWithFlags(&H.evSsm, cudaEventDisableTiming);
      for (int i = 0; i < 8; i++) { cudaEventCreateWithFlags(&H.evA[i], cudaEventDisableTiming); cudaEventCreateWithFlags(&H.evO[i], cudaEventDisableTiming); cudaStreamCreateWithFlags(&H.so[i], cudaStreamNonBlocking); }
      cudaEventCreateWithFlags(&H.evFork, cudaEventDisableTiming);
      cudaEventCreateWithFlags(&H.evJoin, cudaEventDisableTiming);
    }
    H.init = true;
  }
  cudaStream_t s1 = cudaStreamPerThread;
  ChainParams cp;
  cp.Wq = Wq; cp.Wk = Wk; cp.Wv = Wv; cp.Wo = Wo;
  cp.mem0 = mem0; cp.km = km; cp.vm = vm; cp.xbuf = sym_addr(g_xbuf[0]); cp.epoch = sym_addr(g_epoch[0]); cp.kv_flags = sym_addr(g_kvflags[0]);
  cp.m_flags = sym_addr(g_mflags[0]); cp.prof = sym_addr(g_prof[0]);
  GemmParams g1 = {}; g1.tile_begin = 0; g1.tile_end = 352; g1.kblocks = 10; g1.flags = cp.kv_flags;
  SsmParams sp;
  sp.A_re = (const bf16*)d_in[8]; sp.A_im = (const bf16*)d_in[9]; sp.B_re = (const bf16*)d_in[10]; sp.B_im = (const bf16*)d_in[11];
  sp.C_re = (const bf16*)d_in[12]; sp.C_im = (const bf16*)d_in[13]; sp.log_dt = (const bf16*)d_in[14]; sp.Dskip = (const bf16*)d_in[15];
  sp.x = x; sp.gate_w = (const bf16*)d_in[16]; sp.kbf = sym_addr(g_kbf[0]); sp.xT = sym_addr(g_xT[0]); sp.gate = sym_addr(g_gate[0]); sp.bmix = sym_addr(g_bmix[0]);
  AttnParams ap; ap.o_flags = nullptr; ap.kid = 0; ap.rt_begin = 0; ap.m_flags = cp.m_flags; ap.epoch = cp.epoch;
  GemmParams g2 = {}; g2.tile_begin = 0; g2.tile_end = 80; g2.kblocks = 64; g2.gate = sp.gate; g2.bmix = sp.bmix; g2.out = (bf16*)d_out;
  g2.epoch = cp.epoch; g2.bump_epoch = 1;

  cudaStream_t s2 = H.s2, s4 = H.s4;
  launch_ex(chain_kernel, dim3(64), dim3(256), chain::SMEM_BYTES, s1, 16, H.evFork, H.tmWq128, H.tmWk128, H.tmWv128, H.tmWoC, H.tmKV32, cp);
  cudaStreamWaitEvent(H.s3, H.evFork, 0);
  GemmParams g0 = g1; g0.tile_begin = 0; g0.tile_end = 128;
  launch_ex(gemm_kernel<128, 0, 1>, dim3(64), dim3(320), gemm::Cfg<128>::SMEM, H.s3, 1, H.evQ0, H.tmX, H.tmWqB, H.tmWkB, H.tmWvB, H.tmQKVst, g0);
  cudaEventRecord(H.evQ0done, H.s3);
  cudaStreamWaitEvent(s2, H.evQ0, 0);
  launch_ex(gemm_kernel<256, 0, 2>, dim3((H.nsm - 64) & ~1), dim3(320), gemm::Cfg<256>::SMEM, s2, 2, H.evQ, H.tmX, H.tmWqB, H.tmWkB, H.tmWvB, H.tmQKVst, g1);
  cudaStreamWaitEvent(s2, H.evQ0done, 0);
  cudaStreamWaitEvent(s4, H.evQ, 0);
  launch_ex(ssm_gen_kernel, dim3(640 + 64), dim3(256), 0, s4, 1, nullptr, sp);
  launch_ex(conv_kernel, dim3(160), dim3(128), conv::SMEM, s4, 1, nullptr, sp);
  cudaEventRecord(H.evSsm, s4);
  {
    const int bounds[] = CHUNKS;
    const int nch = sizeof(bounds) / sizeof(int) - 1;
    for (int c = 0; c < nch; c++) {
      const int r0 = bounds[c], r1 = bounds[c + 1];
      const bool lastc = (c == nch - 1);
      ap.rt_begin = 2 * r0; ap.kid = 2 * c;
      if (!lastc) launch_ex(gate_kernel, dim3(1), dim3(64), 0, s2, 1, nullptr, (const unsigned*)cp.m_flags, (const unsigned*)cp.epoch, 4 * r1 - 1);
      ap.o_flags = lastc ? sym_addr(g_oflags[0]) : nullptr;
      launch_ex(attn_kernel, dim3(64 * (r1 - r0)), dim3(128), attn::SMEM, s2, 1, lastc ? H.evL : nullptr, H.tmQKV64, H.tmKM, H.tmVM, H.tmOst, ap);
      cudaStream_t so = H.so[c];
      if (lastc) {
        cudaStreamWaitEvent(so, H.evL, 0);
        cudaEventRecord(H.evA[c], s2);
        cudaStreamWaitEvent(s1, H.evA[c], 0);
      } else {
        cudaEventRecord(H.evA[c], s2);
        cudaStreamWaitEvent(so, H.evA[c], 0);
      }
      cudaStreamWaitEvent(so, H.evSsm, 0);
      if (c < nch - NSPLIT) {
        GemmParams gp = g2; gp.tile_begin = 5 * r0; gp.tile_end = 5 * r1; gp.bump_epoch = 0; gp.kid = 2 * c;
        launch_ex(gemm_kernel<128, 1, 1>, dim3(5 * (r1 - r0)), dim3(320), gemm::Cfg<128>::SMEM, so, 1, nullptr, H.tmOA, H.tmWoB, H.tmWoB, H.tmWoB, H.tmOst, gp);
      } else {
        OutParams op; op.rt_begin = r0; op.gate = sp.gate; op.bmix = sp.bmix; op.out = (bf16*)d_out; op.epoch = cp.epoch; op.bump_epoch = lastc; op.kid = 2 * c;
        op.o_flags = ap.o_flags;
        if (lastc && LAST_KS == 8) launch_ex(out_kernel<8>, dim3(5 * (r1 - r0) * 8), dim3(288), outp::Cfg<8>::SMEM, so, 8, nullptr, H.tmOA, H.tmWoB, op);
        else launch_ex(out_kernel<4>, dim3(5 * (r1 - r0) * 4), dim3(288), outp::Cfg<4>::SMEM, so, 4, nullptr, H.tmOA, H.tmWoB, op);
      }
      cudaEventRecord(H.evO[c], so);
      cudaStreamWaitEvent(s1, H.evO[c], 0);
    }
  }
}
```

```cpp
#include <cuda_runtime.h>
#include <cuda_bf16.h>
#include <cuda.h>
#include <stdint.h>

typedef __nv_bfloat16 bf16;

#define DEVINL __device__ __forceinline__

DEVINL uint32_t smem_u32(const void* p) { return (uint32_t)__cvta_generic_to_shared(p); }
DEVINL uint32_t mapa(uint32_t addr, uint32_t rank) {
  uint32_t r; asm volatile("mapa.shared::cluster.u32 %0, %1, %2;" : "=r"(r) : "r"(addr), "r"(rank)); return r;
}
DEVINL void mbar_init(uint32_t bar, int cnt) { asm volatile("mbarrier.init.shared::cta.b64 [%0], %1;" :: "r"(bar), "r"(cnt) : "memory"); }
DEVINL void mbar_expect_tx(uint32_t bar, uint32_t bytes) { asm volatile("mbarrier.arrive.expect_tx.shared::cta.b64 _, [%0], %1;" :: "r"(bar), "r"(bytes) : "memory"); }
DEVINL void mbar_arrive(uint32_t bar) { asm volatile("mbarrier.arrive.shared::cta.b64 _, [%0];" :: "r"(bar) : "memory"); }
DEVINL bool mbar_try_wait(uint32_t bar, uint32_t parity) {
  uint32_t ok;
  asm volatile("{\n.reg .pred p;\nmbarrier.try_wait.parity.shared::cta.b64 p, [%1], %2;\nselp.u32 %0, 1, 0, p;\n}" : "=r"(ok) : "r"(bar), "r"(parity) : "memory");
  return ok;
}
DEVINL bool mbar_try_wait_cluster(uint32_t bar, uint32_t parity) {
  uint32_t ok;
  asm volatile("{\n.reg .pred p;\nmbarrier.try_wait.parity.acquire.cluster.shared::cta.b64 p, [%1], %2;\nselp.u32 %0, 1, 0, p;\n}" : "=r"(ok) : "r"(bar), "r"(parity) : "memory");
  return ok;
}
#define SPIN_LIMIT (1u << 22)
DEVINL void mbar_wait(uint32_t bar, uint32_t parity) {
  uint32_t n = 0;
  while (!mbar_try_wait(bar, parity)) { if (++n > SPIN_LIMIT) __trap(); }
}
DEVINL void mbar_wait_cluster(uint32_t bar, uint32_t parity) {
  uint32_t n = 0;
  while (!mbar_try_wait_cluster(bar, parity)) { if (++n > SPIN_LIMIT) __trap(); }
}
DEVINL void cluster_sync_all() { asm volatile("barrier.cluster.arrive.release.aligned;\nbarrier.cluster.wait.acquire.aligned;" ::: "memory"); }
DEVINL void fence_proxy_async() { asm volatile("fence.proxy.async;" ::: "memory"); }
DEVINL void fence_proxy_async_smem() { asm volatile("fence.proxy.async.shared::cta;" ::: "memory"); }
DEVINL void named_bar_sync(int id, int n) { asm volatile("bar.sync %0, %1;" :: "r"(id), "r"(n) : "memory"); }
DEVINL void named_bar_arrive(int id, int n) { asm volatile("bar.arrive %0, %1;" :: "r"(id), "r"(n) : "memory"); }

DEVINL void st_async_b32(uint32_t raddr, uint32_t v, uint32_t rbar) {
  asm volatile("st.async.weak.shared::cluster.mbarrier::complete_tx::bytes.b32 [%0], %1, [%2];" :: "r"(raddr), "r"(v), "r"(rbar) : "memory");
}
DEVINL void st_async_v2f(uint32_t raddr, float a, float b, uint32_t rbar) {
  asm volatile("st.async.weak.shared::cluster.mbarrier::complete_tx::bytes.v2.f32 [%0], {%1, %2}, [%3];" :: "r"(raddr), "f"(a), "f"(b), "r"(rbar) : "memory");
}
DEVINL void st_async_v4(uint32_t raddr, uint32_t a, uint32_t b, uint32_t c, uint32_t d, uint32_t rbar) {
  asm volatile("st.async.weak.shared::cluster.mbarrier::complete_tx::bytes.v4.b32 [%0], {%1, %2, %3, %4}, [%5];" :: "r"(raddr), "r"(a), "r"(b), "r"(c), "r"(d), "r"(rbar) : "memory");
}

DEVINL void tma_load_2d(uint32_t dst, const CUtensorMap* tm, int c0, int c1, uint32_t bar) {
  asm volatile("cp.async.bulk.tensor.2d.shared::cluster.global.mbarrier::complete_tx::bytes [%0], [%1, {%3, %4}], [%2];"
    :: "r"(dst), "l"(tm), "r"(bar), "r"(c0), "r"(c1) : "memory");
}
DEVINL void bulk_load(uint32_t dst, const void* src, uint32_t bytes, uint32_t bar) {
  asm volatile("cp.async.bulk.shared::cluster.global.mbarrier::complete_tx::bytes [%0], [%1], %2, [%3];" :: "r"(dst), "l"(src), "r"(bytes), "r"(bar) : "memory");
}
DEVINL void tma_prefetch_2d(const CUtensorMap* tm, int c0, int c1) {
  asm volatile("cp.async.bulk.prefetch.tensor.2d.L2.global [%0, {%1, %2}];" :: "l"(tm), "r"(c0), "r"(c1) : "memory");
}
DEVINL void tma_store_2d(const CUtensorMap* tm, uint32_t src, int c0, int c1) {
  asm volatile("cp.async.bulk.tensor.2d.global.shared::cta.bulk_group [%0, {%2, %3}], [%1];"
    :: "l"(tm), "r"(src), "r"(c0), "r"(c1) : "memory");
}
DEVINL void bulk_commit() { asm volatile("cp.async.bulk.commit_group;" ::: "memory"); }
template<int N> DEVINL void bulk_wait_read() { asm volatile("cp.async.bulk.wait_group.read %0;" :: "n"(N) : "memory"); }
template<int N> DEVINL void bulk_wait() { asm volatile("cp.async.bulk.wait_group %0;" :: "n"(N) : "memory"); }
DEVINL void prefetch_tmap(const CUtensorMap* tm) { asm volatile("prefetch.tensormap [%0];" :: "l"(tm) : "memory"); }

DEVINL void ldsm_x4(uint32_t addr, uint32_t& r0, uint32_t& r1, uint32_t& r2, uint32_t& r3) {
  asm volatile("ldmatrix.sync.aligned.m8n8.x4.shared.b16 {%0,%1,%2,%3}, [%4];" : "=r"(r0), "=r"(r1), "=r"(r2), "=r"(r3) : "r"(addr) : "memory");
}
DEVINL void ldsm_x4_t(uint32_t addr, uint32_t& r0, uint32_t& r1, uint32_t& r2, uint32_t& r3) {
  asm volatile("ldmatrix.sync.aligned.m8n8.x4.trans.shared.b16 {%0,%1,%2,%3}, [%4];" : "=r"(r0), "=r"(r1), "=r"(r2), "=r"(r3) : "r"(addr) : "memory");
}
DEVINL void ldsm_x2_t(uint32_t addr, uint32_t& r0, uint32_t& r1) {
  asm volatile("ldmatrix.sync.aligned.m8n8.x2.trans.shared.b16 {%0,%1}, [%2];" : "=r"(r0), "=r"(r1) : "r"(addr) : "memory");
}
DEVINL void stsm_x2_t(uint32_t addr, uint32_t r0, uint32_t r1) {
  asm volatile("stmatrix.sync.aligned.m8n8.x2.trans.shared.b16 [%0], {%1,%2};" :: "r"(addr), "r"(r0), "r"(r1) : "memory");
}
DEVINL void stsm_x4(uint32_t addr, uint32_t r0, uint32_t r1, uint32_t r2, uint32_t r3) {
  asm volatile("stmatrix.sync.aligned.m8n8.x4.shared.b16 [%0], {%1,%2,%3,%4};" :: "r"(addr), "r"(r0), "r"(r1), "r"(r2), "r"(r3) : "memory");
}
DEVINL void mma16816(float* c, uint32_t a0, uint32_t a1, uint32_t a2, uint32_t a3, uint32_t b0, uint32_t b1) {
  asm volatile("mma.sync.aligned.m16n8k16.row.col.f32.bf16.bf16.f32 {%0,%1,%2,%3}, {%4,%5,%6,%7}, {%8,%9}, {%0,%1,%2,%3};"
    : "+f"(c[0]), "+f"(c[1]), "+f"(c[2]), "+f"(c[3]) : "r"(a0), "r"(a1), "r"(a2), "r"(a3), "r"(b0), "r"(b1));
}
DEVINL void mma1688(float* c, uint32_t a0, uint32_t a1, uint32_t b0) {
  asm volatile("mma.sync.aligned.m16n8k8.row.col.f32.bf16.bf16.f32 {%0,%1,%2,%3}, {%4,%5}, {%6}, {%0,%1,%2,%3};"
    : "+f"(c[0]), "+f"(c[1]), "+f"(c[2]), "+f"(c[3]) : "r"(a0), "r"(a1), "r"(b0));
}
DEVINL uint32_t pack_bf16(float lo, float hi) {
  uint32_t r; asm("cvt.rn.bf16x2.f32 %0, %1, %2;" : "=r"(r) : "f"(hi), "f"(lo)); return r;
}
DEVINL float bf16_lo(uint32_t v) { return __uint_as_float(v << 16); }
DEVINL float bf16_hi(uint32_t v) { return __uint_as_float(v & 0xffff0000u); }
DEVINL float round_bf16(float x) { return __bfloat162float(__float2bfloat16_rn(x)); }
DEVINL float ex2(float x) { float r; asm("ex2.approx.ftz.f32 %0, %1;" : "=f"(r) : "f"(x)); return r; }
DEVINL void sts64f(uint32_t addr, float a, float b) { asm volatile("st.shared.v2.f32 [%0], {%1,%2};" :: "r"(addr), "f"(a), "f"(b) : "memory"); }
DEVINL void sts128f(uint32_t addr, const float* v) { asm volatile("st.shared.v4.f32 [%0], {%1,%2,%3,%4};" :: "r"(addr), "f"(v[0]), "f"(v[1]), "f"(v[2]), "f"(v[3]) : "memory"); }
DEVINL void sts32(uint32_t addr, uint32_t v) { asm volatile("st.shared.b32 [%0], %1;" :: "r"(addr), "r"(v) : "memory"); }
DEVINL float2 lds64f(uint32_t addr) { float2 v; asm volatile("ld.shared.v2.f32 {%0,%1}, [%2];" : "=f"(v.x), "=f"(v.y) : "r"(addr) : "memory"); return v; }
DEVINL uint2 lds64u(uint32_t addr) { uint2 v; asm volatile("ld.shared.v2.b32 {%0,%1}, [%2];" : "=r"(v.x), "=r"(v.y) : "r"(addr) : "memory"); return v; }
DEVINL float4 lds128f(uint32_t addr) { float4 v; asm volatile("ld.shared.v4.f32 {%0,%1,%2,%3}, [%4];" : "=f"(v.x), "=f"(v.y), "=f"(v.z), "=f"(v.w) : "r"(addr) : "memory"); return v; }
DEVINL uint4 lds128(uint32_t addr) { uint4 v; asm volatile("ld.shared.v4.b32 {%0,%1,%2,%3}, [%4];" : "=r"(v.x), "=r"(v.y), "=r"(v.z), "=r"(v.w) : "r"(addr) : "memory"); return v; }

#define TS_END_T(k) do {} while (0)
#define TS_BEGIN(k) do {} while (0)
#define TS_END(k) do {} while (0)
DEVINL void wgmma_m64n256k16_tb1(float (&d)[128], uint64_t da, uint64_t db, int scale_d) {
  asm volatile("{\n.reg .pred p;\nsetp.ne.b32 p, %130, 0;\n"
    "wgmma.mma_async.sync.aligned.m64n256k16.f32.bf16.bf16 {%0, %1, %2, %3, %4, %5, %6, %7, %8, %9, %10, %11, %12, %13, %14, %15, %16, %17, %18, %19, %20, %21, %22, %23, %24, %25, %26, %27, %28, %29, %30, %31, %32, %33, %34, %35, %36, %37, %38, %39, %40, %41, %42, %43, %44, %45, %46, %47, %48, %49, %50, %51, %52, %53, %54, %55, %56, %57, %58, %59, %60, %61, %62, %63, %64, %65, %66, %67, %68, %69, %70, %71, %72, %73, %74, %75, %76, %77, %78, %79, %80, %81, %82, %83, %84, %85, %86, %87, %88, %89, %90, %91, %92, %93, %94, %95, %96, %97, %98, %99, %100, %101, %102, %103, %104, %105, %106, %107, %108, %109, %110, %111, %112, %113, %114, %115, %116, %117, %118, %119, %120, %121, %122, %123, %124, %125, %126, %127}, %128, %129, p, 1, 1, 0, 1;\n}\n"
    : "+f"(d[0]), "+f"(d[1]), "+f"(d[2]), "+f"(d[3]), "+f"(d[4]), "+f"(d[5]), "+f"(d[6]), "+f"(d[7]), "+f"(d[8]), "+f"(d[9]), "+f"(d[10]), "+f"(d[11]), "+f"(d[12]), "+f"(d[13]), "+f"(d[14]), "+f"(d[15]), "+f"(d[16]), "+f"(d[17]), "+f"(d[18]), "+f"(d[19]), "+f"(d[20]), "+f"(d[21]), "+f"(d[22]), "+f"(d[23]), "+f"(d[24]), "+f"(d[25]), "+f"(d[26]), "+f"(d[27]), "+f"(d[28]), "+f"(d[29]), "+f"(d[30]), "+f"(d[31]), "+f"(d[32]), "+f"(d[33]), "+f"(d[34]), "+f"(d[35]), "+f"(d[36]), "+f"(d[37]), "+f"(d[38]), "+f"(d[39]), "+f"(d[40]), "+f"(d[41]), "+f"(d[42]), "+f"(d[43]), "+f"(d[44]), "+f"(d[45]), "+f"(d[46]), "+f"(d[47]), "+f"(d[48]), "+f"(d[49]), "+f"(d[50]), "+f"(d[51]), "+f"(d[52]), "+f"(d[53]), "+f"(d[54]), "+f"(d[55]), "+f"(d[56]), "+f"(d[57]), "+f"(d[58]), "+f"(d[59]), "+f"(d[60]), "+f"(d[61]), "+f"(d[62]), "+f"(d[63]), "+f"(d[64]), "+f"(d[65]), "+f"(d[66]), "+f"(d[67]), "+f"(d[68]), "+f"(d[69]), "+f"(d[70]), "+f"(d[71]), "+f"(d[72]), "+f"(d[73]), "+f"(d[74]), "+f"(d[75]), "+f"(d[76]), "+f"(d[77]), "+f"(d[78]), "+f"(d[79]), "+f"(d[80]), "+f"(d[81]), "+f"(d[82]), "+f"(d[83]), "+f"(d[84]), "+f"(d[85]), "+f"(d[86]), "+f"(d[87]), "+f"(d[88]), "+f"(d[89]), "+f"(d[90]), "+f"(d[91]), "+f"(d[92]), "+f"(d[93]), "+f"(d[94]), "+f"(d[95]), "+f"(d[96]), "+f"(d[97]), "+f"(d[98]), "+f"(d[99]), "+f"(d[100]), "+f"(d[101]), "+f"(d[102]), "+f"(d[103]), "+f"(d[104]), "+f"(d[105]), "+f"(d[106]), "+f"(d[107]), "+f"(d[108]), "+f"(d[109]), "+f"(d[110]), "+f"(d[111]), "+f"(d[112]), "+f"(d[113]), "+f"(d[114]), "+f"(d[115]), "+f"(d[116]), "+f"(d[117]), "+f"(d[118]), "+f"(d[119]), "+f"(d[120]), "+f"(d[121]), "+f"(d[122]), "+f"(d[123]), "+f"(d[124]), "+f"(d[125]), "+f"(d[126]), "+f"(d[127])
    : "l"(da), "l"(db), "r"(scale_d));
}
DEVINL void wgmma_m64n128k16_tb1(float (&d)[64], uint64_t da, uint64_t db, int scale_d) {
  asm volatile("{\n.reg .pred p;\nsetp.ne.b32 p, %66, 0;\n"
    "wgmma.mma_async.sync.aligned.m64n128k16.f32.bf16.bf16 {%0, %1, %2, %3, %4, %5, %6, %7, %8, %9, %10, %11, %12, %13, %14, %15, %16, %17, %18, %19, %20, %21, %22, %23, %24, %25, %26, %27, %28, %29, %30, %31, %32, %33, %34, %35, %36, %37, %38, %39, %40, %41, %42, %43, %44, %45, %46, %47, %48, %49, %50, %51, %52, %53, %54, %55, %56, %57, %58, %59, %60, %61, %62, %63}, %64, %65, p, 1, 1, 0, 1;\n}\n"
    : "+f"(d[0]), "+f"(d[1]), "+f"(d[2]), "+f"(d[3]), "+f"(d[4]), "+f"(d[5]), "+f"(d[6]), "+f"(d[7]), "+f"(d[8]), "+f"(d[9]), "+f"(d[10]), "+f"(d[11]), "+f"(d[12]), "+f"(d[13]), "+f"(d[14]), "+f"(d[15]), "+f"(d[16]), "+f"(d[17]), "+f"(d[18]), "+f"(d[19]), "+f"(d[20]), "+f"(d[21]), "+f"(d[22]), "+f"(d[23]), "+f"(d[24]), "+f"(d[25]), "+f"(d[26]), "+f"(d[27]), "+f"(d[28]), "+f"(d[29]), "+f"(d[30]), "+f"(d[31]), "+f"(d[32]), "+f"(d[33]), "+f"(d[34]), "+f"(d[35]), "+f"(d[36]), "+f"(d[37]), "+f"(d[38]), "+f"(d[39]), "+f"(d[40]), "+f"(d[41]), "+f"(d[42]), "+f"(d[43]), "+f"(d[44]), "+f"(d[45]), "+f"(d[46]), "+f"(d[47]), "+f"(d[48]), "+f"(d[49]), "+f"(d[50]), "+f"(d[51]), "+f"(d[52]), "+f"(d[53]), "+f"(d[54]), "+f"(d[55]), "+f"(d[56]), "+f"(d[57]), "+f"(d[58]), "+f"(d[59]), "+f"(d[60]), "+f"(d[61]), "+f"(d[62]), "+f"(d[63])
    : "l"(da), "l"(db), "r"(scale_d));
}
DEVINL void wgmma_fence() { asm volatile("wgmma.fence.sync.aligned;" ::: "memory"); }
DEVINL void wgmma_commit() { asm volatile("wgmma.commit_group.sync.aligned;" ::: "memory"); }
template <int N> DEVINL void wgmma_wait() { asm volatile("wgmma.wait_group.sync.aligned %0;" :: "n"(N) : "memory"); }
DEVINL uint64_t make_desc(uint32_t addr, uint32_t lbo_bytes, uint32_t sbo_bytes) {
  return (uint64_t)((addr & 0x3FFFF) >> 4) | ((uint64_t)(lbo_bytes >> 4) << 16) | ((uint64_t)(sbo_bytes >> 4) << 32) | ((uint64_t)1 << 62);
}
constexpr int DM = 640, NH = 32, DH = 128, SEGL = 32, NSEG = 64, MTOK = 8, HD = NH * DH, SEQ = 2048;

namespace chain {
constexpr int CS = 16, NCL = 4;
constexpr int OFF_WV = 0;
constexpr int OFF_WO = 81920;
constexpr int OFF_KV = 163840;
constexpr int KV_STAGE = 12288;
constexpr int OFF_R = OFF_KV + 2 * KV_STAGE;
constexpr int OFF_MEM = OFF_R + 5120;
constexpr int OFF_PART = OFF_MEM + 10240;
constexpr int OFF_Q = OFF_PART + 6144;
constexpr int OFF_KM = OFF_Q + 1024;
constexpr int OFF_VM = OFF_KM + 1024;
constexpr int OFF_O = OFF_VM + 2048;
constexpr int OFF_SLOC = OFF_O + 2048;
constexpr int OFF_SREM = OFF_SLOC + 1280;
constexpr int OFF_BAR = OFF_SREM + 1280;
constexpr int OFF_PROF = OFF_BAR + 128;
constexpr int SMEM_BYTES = OFF_PROF;
static_assert(SMEM_BYTES <= 232448, "smem");
constexpr int BAR_W0 = 0, BAR_W1 = 8, BAR_KV = 16, BAR_S = 32, BAR_R = 40, BAR_AG = 48;
}

DEVINL void wait_counter(const unsigned* f, unsigned target) {
  unsigned v; uint32_t n = 0;
  while (true) {
    asm volatile("ld.acquire.gpu.global.u32 %0, [%1];" : "=r"(v) : "l"(f) : "memory");
    if ((int)(v - target) >= 0) break;
    __nanosleep(100);
    if (++n > (1u << 24)) __trap();
  }
}
struct ChainParams {
  const bf16 *Wq, *Wk, *Wv, *Wo;
  const bf16* mem0;
  bf16* km;
  bf16* vm;
  uint4* xbuf;
  unsigned* epoch;
  unsigned* kv_flags;
  unsigned* m_flags;
  long long* prof;
};

DEVINL void st128_relaxed(void* p, uint32_t a, uint32_t b, uint32_t c, uint32_t d) {
  asm volatile("{\n.reg .b128 t;\n.reg .b64 lo, hi;\nmov.b64 lo, {%1, %2};\nmov.b64 hi, {%3, %4};\nmov.b128 t, {lo, hi};\nst.relaxed.gpu.global.b128 [%0], t;\n}" :: "l"(p), "r"(a), "r"(b), "r"(c), "r"(d) : "memory");
}
DEVINL void ld128_relaxed(const void* p, uint32_t* v) {
  asm volatile("{\n.reg .b128 t;\n.reg .b64 lo, hi;\nld.relaxed.gpu.global.b128 t, [%4];\nmov.b128 {lo, hi}, t;\nmov.b64 {%0, %1}, lo;\nmov.b64 {%2, %3}, hi;\n}" : "=r"(v[0]), "=r"(v[1]), "=r"(v[2]), "=r"(v[3]) : "l"(p) : "memory");
}
DEVINL void ldsm_x4_ta(uint32_t addr, uint32_t* r) { ldsm_x4_t(addr, r[0], r[1], r[2], r[3]); }
DEVINL void ldsm_x4_a(uint32_t addr, uint32_t* r) { ldsm_x4(addr, r[0], r[1], r[2], r[3]); }
DEVINL void mma_a(float* c, const uint32_t* a, uint32_t b0, uint32_t b1) { mma16816(c, a[0], a[1], a[2], a[3], b0, b1); }
DEVINL void stsm_x4_t(uint32_t addr, uint32_t r0, uint32_t r1, uint32_t r2, uint32_t r3) {
  asm volatile("stmatrix.sync.aligned.m8n8.x4.trans.shared.b16 [%0], {%1,%2,%3,%4};" :: "r"(addr), "r"(r0), "r"(r1), "r"(r2), "r"(r3) : "memory");
}
DEVINL uint32_t clk32() { uint32_t t; asm volatile("mov.u32 %0, %%clock;" : "=r"(t) :: "memory"); return t; }

#ifndef NVP7
#define NVP7 6
#endif
#define PFA 12
#define PFB 8
#define FIRST_DELAY 500
#define XSLOTS 2
#define RETRY_DELAY 0
#define POLL_GAP 170
#define PROF(pt) do {} while (0)

template <int NT, int PF>
struct WoState {
  uint32_t wa[PF][4];
  uint32_t addr[NT];
};
template <int NT, int PF>
DEVINL void wo_prepare(WoState<NT, PF>& w, uint32_t sb, uint32_t A0, int mt0) {
  using namespace chain;
#pragma unroll
  for (int i = 0; i < NT; i++) {
    const int mt = mt0 + 8 * i;
    w.addr[i] = sb + OFF_WO + (mt >> 2) * 16384 + (A0 ^ ((mt & 3) << 5));
  }
#pragma unroll
  for (int f = 0; f < PF; f++) ldsm_x4_ta(w.addr[f / 8] + (f % 8) * 2048, w.wa[f]);
}
template <int NT, int PF>
DEVINL void wo_phase(WoState<NT, PF>& w, uint32_t sb, uint32_t c_ld, uint32_t rdst0, uint32_t rbar0, uint32_t cstride, int mt0) {
  using namespace chain;
  uint32_t ob[16];
#pragma unroll
  for (int i = 0; i < 4; i++) ldsm_x4_a(sb + OFF_O + (i >> 1) * 1024 + (c_ld ^ ((i & 1) * 64)), ob + 4 * i);
#pragma unroll
  for (int i = 0; i < NT; i++) {
    float c0[4] = {0.f, 0.f, 0.f, 0.f}, c1[4] = {0.f, 0.f, 0.f, 0.f};
#pragma unroll
    for (int ks = 0; ks < 8; ks++) {
      const int f = i * 8 + ks;
      mma_a((ks & 1) ? c1 : c0, w.wa[f % PF], ob[2 * ks], ob[2 * ks + 1]);
      if (f + PF < NT * 8) ldsm_x4_ta(w.addr[(f + PF) / 8] + ((f + PF) % 8) * 2048, w.wa[f % PF]);
    }
#pragma unroll
    for (int hh = 0; hh < 2; hh++) {
      const int cg = 2 * (mt0 + 8 * i) + hh;
      const int own = (cg * 13) >> 6;
      const uint32_t ooff = own * cstride;
      st_async_b32(rdst0 + ooff + (cg - own * 5) * 128, pack_bf16(c0[2 * hh] + c1[2 * hh], c0[2 * hh + 1] + c1[2 * hh + 1]), rbar0 + ooff);
    }
  }
}

__global__ void __launch_bounds__(256, 1) chain_kernel(
    const __grid_constant__ CUtensorMap tmWq, const __grid_constant__ CUtensorMap tmWk,
    const __grid_constant__ CUtensorMap tmWv, const __grid_constant__ CUtensorMap tmWo,
    const __grid_constant__ CUtensorMap tmKV, ChainParams p) {
  using namespace chain;
  extern __shared__ __align__(1024) uint8_t smem_raw[];
  const uint32_t sb = smem_u32(smem_raw);
  const int tid = threadIdx.x;
  const int lane = __shfl_sync(0xffffffffu, tid & 31, tid & 31);
  const int warp = __shfl_sync(0xffffffffu, tid >> 5, 0);
  const int kh = warp >> 2, mg = warp & 3;
  uint32_t rank; asm volatile("mov.u32 %0, %%cluster_ctarank;" : "=r"(rank));
  const int g = blockIdx.x / CS;
  const int head = g * 8 + (rank >> 1), half = rank & 1;
  const int colbase = head * DH + half * 64;
  const uint32_t bars = sb + OFF_BAR;
  TS_BEGIN(0);

  asm volatile("griddepcontrol.launch_dependents;" ::: "memory");
  const unsigned epoch = *(volatile unsigned*)p.epoch;
  const unsigned tagbase = epoch * 64u;

  if (tid == 0) {
    mbar_init(bars + BAR_W0, 1); mbar_init(bars + BAR_W1, 1);
    for (int i = 0; i < 2; i++) mbar_init(bars + BAR_KV + 8 * i, 1);
    mbar_init(bars + BAR_S, 10); mbar_init(bars + BAR_R, 1);
    for (int i = 0; i < 8; i++) mbar_init(bars + BAR_AG + 8 * i, 1);
    asm volatile("fence.mbarrier_init.release.cluster;" ::: "memory");
    fence_proxy_async();
    mbar_expect_tx(bars + BAR_S, 1280 + 1024);
  }
  __syncthreads();
  asm volatile("barrier.cluster.arrive.release.aligned;" ::: "memory");
  if (tid == 224) {
    mbar_expect_tx(bars + BAR_W0, 163840);
    for (int i = 0; i < 5; i++) tma_load_2d(sb + OFF_WV + i * 16384, &tmWq, colbase, 128 * i, bars + BAR_W0);
    for (int i = 0; i < 5; i++) tma_load_2d(sb + OFF_WO + i * 16384, &tmWk, colbase, 128 * i, bars + BAR_W0);
  }
  if (tid >= 192 && tid < 192 + 20) {
    const int j = tid - 192, m = j / 5, c = j % 5;
    const bf16* base = (m == 0) ? p.Wk : (m == 1) ? p.Wq : (m == 2) ? p.Wv : p.Wo;
    const char* src = reinterpret_cast<const char*>(base) + (size_t)blockIdx.x * 81920 + c * 16384;
    asm volatile("cp.async.bulk.prefetch.L2.global [%0], %1;" :: "l"(src), "r"(16384) : "memory");
    if (j == 0) prefetch_tmap(&tmKV);
    if (j == 1) prefetch_tmap(&tmWv);
    if (j == 2) prefetch_tmap(&tmWo);
  }
  {
    if (tid < 160) {
      uint2 v[8];
#pragma unroll
      for (int t = 0; t < 8; t++) v[t] = __ldg(reinterpret_cast<const uint2*>(p.mem0 + t * DM + tid * 4));
#pragma unroll
      for (int c = 0; c < 4; c++) {
        uint32_t w[4];
#pragma unroll
        for (int t2 = 0; t2 < 4; t2++) {
          const uint32_t a = (c < 2) ? v[2 * t2].x : v[2 * t2].y, b = (c < 2) ? v[2 * t2 + 1].x : v[2 * t2 + 1].y;
          w[t2] = (c & 1) ? __byte_perm(a, b, 0x7632) : __byte_perm(a, b, 0x5410);
        }
        asm volatile("st.shared.v4.b32 [%0], {%1,%2,%3,%4};" :: "r"(sb + OFF_MEM + (tid * 4 + c) * 16), "r"(w[0]), "r"(w[1]), "r"(w[2]), "r"(w[3]) : "memory");
      }
    }
  }

  const uint32_t A0 = (uint32_t)(((lane >> 4) * 8 + (lane & 7)) * 128 + ((((lane >> 3) & 1) ^ (lane & 7)) << 4));
  const uint32_t c_ld = (lane & 7) * 128 + (((lane >> 3) ^ (lane & 7)) << 4);
  const uint32_t a_lane = A0 ^ (mg << 5);
  uint32_t wq[20][4], wk[20][4];
  mbar_wait(bars + BAR_W0, 0);
#pragma unroll
  for (int kk = 0; kk < 20; kk++) {
    ldsm_x4_ta(sb + OFF_WV + (20 * kh + kk) * 2048 + a_lane, wq[kk]);
    ldsm_x4_ta(sb + OFF_WO + (20 * kh + kk) * 2048 + a_lane, wk[kk]);
  }
  __syncthreads();
  if (tid == 0) {
    fence_proxy_async();
    mbar_expect_tx(bars + BAR_W1, 163840);
    for (int i = 0; i < 5; i++) tma_load_2d(sb + OFF_WV + i * 16384, &tmWv, colbase, 128 * i, bars + BAR_W1);
    for (int i = 0; i < 5; i++) tma_load_2d(sb + OFF_WO + i * 16384, &tmWo, 320 * half + 64 * i, head * DH, bars + BAR_W1);
    if (p.kv_flags) {
      wait_counter(p.kv_flags + head, 2 * (epoch + 1));
      wait_counter(p.kv_flags + 32 + head, 2 * (epoch + 1));
      fence_proxy_async();
    }
    for (int s2 = 0; s2 < 2; s2++) {
      const uint32_t d = sb + OFF_KV + s2 * KV_STAGE;
      mbar_expect_tx(bars + BAR_KV + 8 * s2, KV_STAGE);
      tma_load_2d(d, &tmKV, HD + colbase, 32 * s2, bars + BAR_KV + 8 * s2);
      tma_load_2d(d + 4096, &tmKV, 2 * HD + head * DH, 32 * s2, bars + BAR_KV + 8 * s2);
      tma_load_2d(d + 8192, &tmKV, 2 * HD + head * DH + 64, 32 * s2, bars + BAR_KV + 8 * s2);
    }
  }
  const uint32_t cstride_ = mapa(sb, 1) - mapa(sb, 0);
  const uint32_t sb0_ = mapa(sb, 0);
  const uint32_t mem_lane = sb + OFF_MEM + (kh * 320 + lane) * 16;
  const uint32_t wv_lane = sb + OFF_WV + kh * 20 * 2048 + a_lane;
  __syncthreads();
  asm volatile("barrier.cluster.wait.acquire.aligned;" ::: "memory");
  mbar_wait(bars + BAR_W1, 0);

  constexpr int NVP = NVP7;
  for (int s = 0; s < NSEG; s++) {
    const uint32_t ph = s & 1;
    const bool last = (s == NSEG - 1);
    PROF(0);
    uint32_t vp[NVP][4];
#pragma unroll
    for (int i = 0; i < NVP; i++) ldsm_x4_ta(wv_lane + i * 2048, vp[i]);
    if (warp == 3 && !last) mbar_wait(bars + BAR_KV + 8 * ph, (s >> 1) & 1);
    float aq[4] = {0.f, 0.f, 0.f, 0.f}, ak[4] = {0.f, 0.f, 0.f, 0.f}, av[4] = {0.f, 0.f, 0.f, 0.f};
    uint32_t bb[2][4];
    if (s > 0) mbar_wait(bars + BAR_AG + 32 * kh, ph ^ 1);
    PROF(1);
    ldsm_x4_ta(mem_lane, bb[0]);
#pragma unroll
    for (int pp = 0; pp < 10; pp++) {
      uint32_t v0[4], v1[4];
      if (s > 0) {
        if (pp == 1) mbar_wait(bars + BAR_AG + 32 * kh + 8, ph ^ 1);
        if (pp == 4) mbar_wait(bars + BAR_AG + 32 * kh + 16, ph ^ 1);
        if (pp == 6) mbar_wait(bars + BAR_AG + 32 * kh + 24, ph ^ 1);
      }
      if (pp < 9) ldsm_x4_ta(mem_lane + (pp + 1) * 512, bb[(pp + 1) & 1]);
      if (2 * pp >= NVP) {
        ldsm_x4_ta(wv_lane + (2 * pp) * 2048, v0);
        ldsm_x4_ta(wv_lane + (2 * pp + 1) * 2048, v1);
      } else {
#pragma unroll
        for (int e = 0; e < 4; e++) { v0[e] = vp[2 * pp][e]; v1[e] = vp[2 * pp + 1][e]; }
      }
      const uint32_t* b = bb[pp & 1];
      mma_a(aq, wq[2 * pp], b[0], b[1]);
      mma_a(ak, wk[2 * pp], b[0], b[1]);
      mma_a(av, v0, b[0], b[1]);
      mma_a(aq, wq[2 * pp + 1], b[2], b[3]);
      mma_a(ak, wk[2 * pp + 1], b[2], b[3]);
      mma_a(av, v1, b[2], b[3]);
    }
    PROF(2);
    uint32_t cstride = cstride_, sb0 = sb0_;
    asm volatile("" : "+r"(cstride), "+r"(sb0));
    const uint32_t partner_base = sb0 + (rank ^ 1) * cstride;
    const uint32_t kvs = sb + OFF_KV + ph * KV_STAGE;
    const uint32_t pbase = sb + OFF_PART + mg * 1536 + lane * 16;
    const uint32_t st_off = (A0 ^ (mg << 5)) & 0x3ffu;
    const uint32_t s_off = ((lane >> 2) * 40 + (lane & 3) * 2) * 4;
    const uint32_t q_ld = (lane & 7) * 128 + (((lane >> 4) ^ (lane & 7)) << 4);
    if (warp < 4) {
      sts128f(pbase + 1024, av);
      named_bar_sync(1 + mg, 64);
      {
        float4 a = lds128f(pbase), b = lds128f(pbase + 512);
        stsm_x2_t(sb + OFF_Q + st_off, pack_bf16(aq[0] + a.x, aq[1] + a.y), pack_bf16(aq[2] + a.z, aq[3] + a.w));
        stsm_x2_t(sb + OFF_KM + st_off, pack_bf16(ak[0] + b.x, ak[1] + b.y), pack_bf16(ak[2] + b.z, ak[3] + b.w));
      }
      named_bar_sync(5, 160);
      PROF(3);
    } else {
      sts128f(pbase, aq); sts128f(pbase + 512, ak);
      named_bar_sync(1 + mg, 64);
      float4 a = lds128f(pbase + 1024);
      const uint32_t vo = OFF_VM + half * 1024 + st_off;
      stsm_x2_t(sb + vo, pack_bf16(av[0] + a.x, av[1] + a.y), pack_bf16(av[2] + a.z, av[3] + a.w));
      if (!last) {
        __syncwarp();
        if (lane < 16) {
          uint4 v = lds128(sb + vo);
          st_async_v4(partner_base + vo, v.x, v.y, v.z, v.w, partner_base + OFF_BAR + BAR_S);
        }
        if (lane == 0) mbar_arrive(bars + BAR_S);
      }
      if (warp == 4) named_bar_sync(5, 160);
      PROF(3);
    }
    if (!last) {
      if (warp < 5) {
        uint32_t q[4][4], k[8];
        const uint32_t kb = (warp < 4) ? (kvs + warp * 1024) : (sb + OFF_KM);
#pragma unroll
        for (int ks = 0; ks < 4; ks++) ldsm_x4_a(sb + OFF_Q + (q_ld ^ (ks << 5)), q[ks]);
        ldsm_x4_a(kb + c_ld, k);
        ldsm_x4_a(kb + (c_ld ^ 64), k + 4);
        float s0[4] = {0.f, 0.f, 0.f, 0.f}, s1[4] = {0.f, 0.f, 0.f, 0.f};
        mma_a(s0, q[0], k[0], k[1]);
        mma_a(s1, q[1], k[2], k[3]);
        mma_a(s0, q[2], k[4], k[5]);
        mma_a(s1, q[3], k[6], k[7]);
        const float x = s0[0] + s1[0], y = s0[1] + s1[1];
        st_async_v2f(partner_base + OFF_SREM + s_off + warp * 32, x, y, partner_base + OFF_BAR + BAR_S);
        sts64f(sb + OFF_SLOC + s_off + warp * 32, x, y);
        __syncwarp();
        if (lane == 0) mbar_arrive(bars + BAR_S);
      }
      PROF(4);
      const uint32_t rdst0 = sb0 + (8 * half) * cstride + OFF_R + (rank >> 1) * 640 + (lane >> 2) * 16 + (lane & 3) * 4;
      const uint32_t rbar0 = sb0 + (8 * half) * cstride + OFF_BAR + BAR_R;
      if (warp < 4) {
        if (warp == 2 && lane == 0) {
          mbar_expect_tx(bars + BAR_R, 5120);
#pragma unroll
          for (int i = 0; i < 8; i++) mbar_expect_tx(bars + BAR_AG + 8 * i, 1280);
        }
        WoState<3, PFA> w;
        wo_prepare<3, PFA>(w, sb, A0, warp);
        __syncthreads();
        PROF(6);
        wo_phase<3, PFA>(w, sb, c_ld, rdst0, rbar0, cstride, warp);
        PROF(7);
        if (warp == 0) {
          if (lane == 0 && s + 2 < NSEG - 1) {
            const int s2 = s + 2;
            const uint32_t d = sb + OFF_KV + ph * KV_STAGE;
            if (p.kv_flags && (s2 & 3) == 0) {
              wait_counter(p.kv_flags + (s2 >> 2) * 64 + head, 2 * (epoch + 1));
              wait_counter(p.kv_flags + (s2 >> 2) * 64 + 32 + head, 2 * (epoch + 1));
              fence_proxy_async();
            }
            mbar_expect_tx(bars + BAR_KV + 8 * ph, KV_STAGE);
            tma_load_2d(d, &tmKV, HD + colbase, 32 * s2, bars + BAR_KV + 8 * ph);
            tma_load_2d(d + 4096, &tmKV, 2 * HD + head * DH, 32 * s2, bars + BAR_KV + 8 * ph);
            tma_load_2d(d + 8192, &tmKV, 2 * HD + head * DH + 64, 32 * s2, bars + BAR_KV + 8 * ph);
          }
        } else if (warp == 3) {
          if (lane == 0 && s + 1 < NSEG - 1) mbar_expect_tx(bars + BAR_S, 1280 + 1024);
        }
      } else {
        const int wi = warp - 4;
        WoState<2, PFB> w;
        {
          const uint32_t vt = kvs + 4096 + (wi >> 1) * 4096;
          const uint32_t vx = ((wi & 1) * 2) << 5;
          uint32_t va[2][2][4], vmb[4];
          mbar_wait(bars + BAR_KV + 8 * ph, (s >> 1) & 1);
#pragma unroll
          for (int i = 0; i < 2; i++)
#pragma unroll
            for (int ks = 0; ks < 2; ks++) ldsm_x4_ta(vt + ks * 2048 + (A0 ^ (vx + (i << 5))), va[i][ks]);
          mbar_wait(bars + BAR_S, ph);
          PROF(5);
          ldsm_x4_ta(sb + OFF_VM + (wi >> 1) * 1024 + (c_ld ^ ((wi & 1) * 64)), vmb);
          float sv[10];
          float mx = -INFINITY;
#pragma unroll
          for (int j = 0; j < 5; j++) {
            float2 a = lds64f(sb + OFF_SLOC + s_off + j * 32), b = lds64f(sb + OFF_SREM + s_off + j * 32);
            sv[2 * j] = a.x + b.x; sv[2 * j + 1] = a.y + b.y;
            mx = fmaxf(mx, fmaxf(sv[2 * j], sv[2 * j + 1]));
          }
          mx = fmaxf(mx, __shfl_xor_sync(0xffffffffu, mx, 1));
          mx = fmaxf(mx, __shfl_xor_sync(0xffffffffu, mx, 2));
          const float sc = 0.08838834764831845f * 1.4426950408889634f;
          const float mo = -mx * sc;
          uint32_t pa[5];
#pragma unroll
          for (int j = 0; j < 5; j++) pa[j] = pack_bf16(ex2(fmaf(sv[2 * j], sc, mo)), ex2(fmaf(sv[2 * j + 1], sc, mo)));
          float o[2][4], sm[4] = {0.f, 0.f, 0.f, 0.f};
          const uint32_t one = 0x3f803f80u;
#pragma unroll
          for (int i = 0; i < 2; i++) { o[i][0] = o[i][1] = o[i][2] = o[i][3] = 0.f; }
          mma16816(sm, one, one, one, one, pa[0], pa[1]);
          mma_a(o[0], va[0][0], pa[0], pa[1]);
          mma_a(o[1], va[1][0], pa[0], pa[1]);
          mma16816(sm, one, one, one, one, pa[2], pa[3]);
          mma_a(o[0], va[0][1], pa[2], pa[3]);
          mma_a(o[1], va[1][1], pa[2], pa[3]);
          mma1688(sm, one, one, pa[4]);
          mma1688(o[0], vmb[0], vmb[1], pa[4]);
          mma1688(o[1], vmb[2], vmb[3], pa[4]);
          const float i0 = __fdividef(1.0f, sm[0]), i1 = __fdividef(1.0f, sm[1]);
          stsm_x4_t(sb + OFF_O + (wi >> 1) * 1024 + (c_ld ^ ((wi & 1) * 64)),
                    pack_bf16(o[0][0] * i0, o[0][1] * i1), pack_bf16(o[0][2] * i0, o[0][3] * i1),
                    pack_bf16(o[1][0] * i0, o[1][1] * i1), pack_bf16(o[1][2] * i0, o[1][3] * i1));
        }
        wo_prepare<2, PFB>(w, sb, A0, warp);
        __syncthreads();
        PROF(6);
        wo_phase<2, PFB>(w, sb, c_ld, rdst0, rbar0, cstride, warp);
        PROF(7);
        const int t80 = wi * 32 + lane;
        if (t80 < 80) {
          uint4* xb = p.xbuf + (size_t)((XSLOTS == 2 ? ph : (uint32_t)(s % XSLOTS)) * NCL) * (CS * 80) + rank * 80 + t80;
          const uint4* x1 = xb + ((g + 1) & 3) * (CS * 80);
          const uint4* x2 = xb + ((g + 2) & 3) * (CS * 80);
          const uint4* x3 = xb + ((g + 3) & 3) * (CS * 80);
          uint4* x0 = xb + g * (CS * 80);
          uint32_t ra = sb + OFF_R + t80 * 8;
          uint32_t tag = tagbase + s + 1;
          uint32_t mo[8], bo[8];
#pragma unroll
          for (int i = 0; i < 8; i++) {
            const uint32_t d = ((lane & 1) * 8 + ((i + rank) & 7)) * cstride;
            mo[i] = sb0 + OFF_MEM + (rank * 40 + (t80 >> 1)) * 16 + d;
            bo[i] = sb0 + OFF_BAR + BAR_AG + (rank >> 1) * 8 + d;
          }
          asm volatile("" : "+l"(x0), "+l"(x1), "+l"(x2), "+l"(x3), "+r"(ra), "+r"(tag));
          asm volatile("" : "+r"(mo[0]), "+r"(mo[1]), "+r"(mo[2]), "+r"(mo[3]), "+r"(mo[4]), "+r"(mo[5]), "+r"(mo[6]), "+r"(mo[7]));
          asm volatile("" : "+r"(bo[0]), "+r"(bo[1]), "+r"(bo[2]), "+r"(bo[3]), "+r"(bo[4]), "+r"(bo[5]), "+r"(bo[6]), "+r"(bo[7]));
          mbar_wait(bars + BAR_R, ph);
          PROF(8);
          float4 a;
          {
            uint2 v[8];
#pragma unroll
            for (int src_ = 0; src_ < 8; src_++) v[src_] = lds64u(ra + src_ * 640);
            a.x = ((bf16_lo(v[0].x) + bf16_lo(v[1].x)) + (bf16_lo(v[2].x) + bf16_lo(v[3].x))) + ((bf16_lo(v[4].x) + bf16_lo(v[5].x)) + (bf16_lo(v[6].x) + bf16_lo(v[7].x)));
            a.y = ((bf16_hi(v[0].x) + bf16_hi(v[1].x)) + (bf16_hi(v[2].x) + bf16_hi(v[3].x))) + ((bf16_hi(v[4].x) + bf16_hi(v[5].x)) + (bf16_hi(v[6].x) + bf16_hi(v[7].x)));
            a.z = ((bf16_lo(v[0].y) + bf16_lo(v[1].y)) + (bf16_lo(v[2].y) + bf16_lo(v[3].y))) + ((bf16_lo(v[4].y) + bf16_lo(v[5].y)) + (bf16_lo(v[6].y) + bf16_lo(v[7].y)));
            a.w = ((bf16_hi(v[0].y) + bf16_hi(v[1].y)) + (bf16_hi(v[2].y) + bf16_hi(v[3].y))) + ((bf16_hi(v[4].y) + bf16_hi(v[5].y)) + (bf16_hi(v[6].y) + bf16_hi(v[7].y)));
          }
          const uint32_t u0 = __float_as_uint(a.x) + 0x80u, u1 = __float_as_uint(a.y) + 0x80u, u2 = __float_as_uint(a.z) + 0x80u, u3 = __float_as_uint(a.w) + 0x80u;
          uint32_t r[4][4], r2[3][4];
          r[0][0] = __byte_perm(u0, u3, 0x3217); r[0][1] = __byte_perm(u1, u3, 0x3216); r[0][2] = __byte_perm(u2, u3, 0x3215);
          st128_relaxed(x0, r[0][0], r[0][1], r[0][2], tag);
          PROF(9);
          {
            uint32_t n = 0;
            { const uint32_t t0 = clk32(); while (clk32() - t0 < FIRST_DELAY) {} }
            while (true) {
              ld128_relaxed(x1, r[1]); ld128_relaxed(x2, r[2]); ld128_relaxed(x3, r[3]);
              if (r[1][3] == tag && r[2][3] == tag && r[3][3] == tag) break;
              if (++n > SPIN_LIMIT) __trap();
            }
          }
          PROF(10);
          float fin[4];
#pragma unroll
          for (int e = 0; e < 4; e++) {
            float f[4];
#pragma unroll
            for (int d = 0; d < 4; d++)
              f[d] = (e < 3) ? __uint_as_float(r[d][e])
                             : __uint_as_float(__byte_perm(__byte_perm(r[d][0], r[d][1], 0x0440), r[d][2], 0x3244) );
            fin[e] = (f[0] + f[2]) + (f[1] + f[3]);
          }
          const uint32_t lo = pack_bf16(fin[0], fin[1]), hi = pack_bf16(fin[2], fin[3]);
          const unsigned am = (warp == 6) ? 0x0000ffffu : 0xffffffffu;
          const uint32_t olo = __shfl_xor_sync(am, lo, 1), ohi = __shfl_xor_sync(am, hi, 1);
          const bool odd = lane & 1;
          const uint32_t w_0 = odd ? olo : lo, w_1 = odd ? ohi : hi, w_2 = odd ? lo : olo, w_3 = odd ? hi : ohi;
#pragma unroll
          for (int i = 0; i < 8; i++) st_async_v4(mo[i], w_0, w_1, w_2, w_3, bo[i]);
          PROF(11);
        }
      }
    } else {
      __syncthreads();
    }
    if (warp == 1) {
      const uint8_t* sp = smem_raw;
#pragma unroll
      for (int i = 0; i < 4; i++) {
        const int idx = lane + 32 * i;
        const int isv = idx >> 6, r = (idx >> 3) & 7, ch = idx & 7;
        uint4 v = *reinterpret_cast<const uint4*>(sp + (isv ? OFF_VM + half * 1024 : OFF_KM) + r * 128 + ((ch ^ r) << 4));
        bf16* dst = (isv ? p.vm : p.km) + ((size_t)(s * MTOK + r)) * HD + colbase + ch * 8;
        *reinterpret_cast<uint4*>(dst) = v;
      }
      __syncwarp();
      if (lane == 0) {
        asm volatile("fence.acq_rel.gpu;" ::: "memory");
        asm volatile("st.relaxed.gpu.global.u32 [%0], %1;" :: "l"(p.m_flags + s * 64 + blockIdx.x), "r"(epoch + 1) : "memory");
      }
    }
    PROF(12);
  }
  __syncthreads();
  TS_END(0);
  cluster_sync_all();
}
namespace gemm {
constexpr int BM = 128, BK = 64;
template <int BN> struct Cfg {
  static constexpr int STAGES = (BN == 256) ? 4 : 6;
  static constexpr int A_BYTES = BM * BK * 2;
  static constexpr int B_BYTES = BK * BN * 2;
  static constexpr int STAGE_BYTES = A_BYTES + B_BYTES;
  static constexpr int EPI_BYTES = 32768;
  static constexpr int OFF_EPI = STAGES * STAGE_BYTES;
  static constexpr int OFF_BAR = OFF_EPI + EPI_BYTES;
  static constexpr int SMEM = OFF_BAR + 256;
};
}

struct GemmParams {
  int tile_begin, tile_end;
  int kblocks;
  unsigned* flags;
  const float* gate;
  const bf16* bmix;
  bf16* out;
  unsigned* epoch;
  int bump_epoch;
  int kid;
};

template <int BN, int EPI, int CM>
DEVINL void tile_coords(int t, int rank, int& rt, int& ct) {
  if (EPI == 0) {
    if (BN == 128) { rt = t >> 6; ct = 32 + (t & 63); }
    else {
      if (t < 224) { rt = 1 + (t >> 5); ct = 16 + (t & 31); }
      else { t -= 224; rt = t >> 4; ct = t & 15; }
      rt = rt * 2 + rank;
    }
  } else { rt = t / 5; ct = t % 5; }
}
DEVINL void tma_load_2d_mc(uint32_t dst, const CUtensorMap* tm, int c0, int c1, uint32_t bar, uint16_t mask) {
  asm volatile("cp.async.bulk.tensor.2d.shared::cluster.global.mbarrier::complete_tx::bytes.multicast::cluster [%0], [%1, {%3, %4}], [%2], %5;"
    :: "r"(dst), "l"(tm), "r"(bar), "r"(c0), "r"(c1), "h"(mask) : "memory");
}
DEVINL void mbar_arrive_remote(uint32_t cluster_addr) {
  asm volatile("mbarrier.arrive.shared::cluster.b64 _, [%0];" :: "r"(cluster_addr) : "memory");
}

template <int BN, int EPI, int CM>
__global__ void __launch_bounds__(320, 1) gemm_kernel(const __grid_constant__ CUtensorMap tmA, const __grid_constant__ CUtensorMap tmB0,
                                                       const __grid_constant__ CUtensorMap tmB1, const __grid_constant__ CUtensorMap tmB2,
                                                       const __grid_constant__ CUtensorMap tmC, GemmParams p) {
  using C = gemm::Cfg<BN>;
  extern __shared__ __align__(1024) uint8_t smem_raw[];
  const uint32_t sb = smem_u32(smem_raw);
  const int tid = threadIdx.x, warp = tid >> 5, lane = tid & 31;
  const uint32_t bar_full = sb + C::OFF_BAR, bar_empty = bar_full + 8 * C::STAGES;
  const uint32_t bar_sfull = bar_empty + 8 * C::STAGES, bar_sempty = bar_sfull + 32;
  TS_BEGIN(EPI == 0 ? 1 : 5 + p.kid);
  uint32_t crank = 0;
  if (CM > 1) asm volatile("mov.u32 %0, %%cluster_ctarank;" : "=r"(crank));
  const int cid = blockIdx.x / CM, ncl = gridDim.x / CM;
  if (tid == 0) {
    for (int i = 0; i < C::STAGES; i++) { mbar_init(bar_full + 8 * i, 1); mbar_init(bar_empty + 8 * i, 2 * CM); }
    for (int i = 0; i < 4; i++) { mbar_init(bar_sfull + 8 * i, 128); mbar_init(bar_sempty + 8 * i, 1); }
    asm volatile("fence.mbarrier_init.release.cluster;" ::: "memory");
    fence_proxy_async();
  }
  __syncthreads();
  if (CM > 1) cluster_sync_all();
  if (warp == 8) {
    if (lane == 0) {
      prefetch_tmap(&tmA); prefetch_tmap(&tmB0);
      int st = 0; uint32_t ph = 0;
      for (int t = p.tile_begin + cid; t < p.tile_end; t += ncl) {
        int rt, ct; tile_coords<BN, EPI, CM>(t, crank, rt, ct);
        const CUtensorMap* tb = &tmB0;
        int bcol = ct * BN;
        if (EPI == 0) { constexpr int PER = 4096 / BN; tb = (ct < PER) ? &tmB0 : (ct < 2 * PER) ? &tmB1 : &tmB2; bcol = (ct % PER) * BN; }
        for (int kb = 0; kb < p.kblocks; kb++) {
          mbar_wait(bar_empty + 8 * st, ph ^ 1);
          const uint32_t sa = sb + st * C::STAGE_BYTES, sbb = sa + C::A_BYTES;
          mbar_expect_tx(bar_full + 8 * st, C::STAGE_BYTES);
          tma_load_2d(sa, &tmA, kb * 64, rt * 128, bar_full + 8 * st);
          if (CM == 1) {
#pragma unroll
            for (int j = 0; j < BN / 64; j++) tma_load_2d(sbb + j * 8192, tb, bcol + j * 64, kb * 64, bar_full + 8 * st);
          } else {
#pragma unroll
            for (int jj = 0; jj < BN / 64 / CM; jj++) {
              const int j = crank * (BN / 64 / CM) + jj;
              tma_load_2d_mc(sbb + j * 8192, tb, bcol + j * 64, kb * 64, bar_full + 8 * st, (uint16_t)((1 << CM) - 1));
            }
          }
          if (++st == C::STAGES) { st = 0; ph ^= 1; }
        }
      }
    }
  } else if (warp == 9) {
    if (EPI == 0 && lane < 2) {
      const int wg = lane;
      const uint32_t stg = sb + C::OFF_EPI + wg * 16384;
      uint32_t ph = 0;
      for (int t = p.tile_begin + cid; t < p.tile_end; t += ncl) {
        int rt, ct; tile_coords<BN, EPI, CM>(t, crank, rt, ct);
#pragma unroll
        for (int j = 0; j < BN / 64; j++) {
          const int slot = j & 1;
          mbar_wait(bar_sfull + 8 * (2 * wg + slot), (ph + (j >> 1)) & 1);
          tma_store_2d(&tmC, stg + slot * 8192, ct * BN + j * 64, rt * 128 + wg * 64);
          bulk_commit();
          if (j >= 1) { bulk_wait_read<1>(); mbar_arrive(bar_sempty + 8 * (2 * wg + (slot ^ 1))); }
        }
        bulk_wait_read<0>();
        mbar_arrive(bar_sempty + 8 * (2 * wg + 1));
        if (BN == 128) ph ^= 1;
        if (ct * BN >= HD) {
          bulk_wait<0>(); __threadfence();
          const int f0 = (ct * BN - HD) / 128;
          atomicAdd(p.flags + rt * 64 + f0, 1u);
          if (BN == 256) atomicAdd(p.flags + rt * 64 + f0 + 1, 1u);
        }
      }
      bulk_wait<0>();
    }
  } else {
    const int wg = warp >> 2;
#define RELEASE(stg_) do { if (CM == 1) { if ((tid & 127) == 0) mbar_arrive(bar_empty + 8 * (stg_)); } \
                           else if ((tid & 127) < CM) mbar_arrive_remote(mapa(bar_empty + 8 * (stg_), tid & 127)); } while (0)
    int st = 0; uint32_t ph = 0, sph = 0;
    float acc[BN / 2];
    for (int t = p.tile_begin + cid; t < p.tile_end; t += ncl) {
      int rt, ct; tile_coords<BN, EPI, CM>(t, crank, rt, ct);
      int prev = -1;
      uint32_t bpre[EPI == 1 ? BN / 8 : 1][2];
      float g0 = 0.f, g1 = 0.f;
      for (int kb = 0; kb < p.kblocks; kb++) {
        if constexpr (EPI == 1) {
          if (kb == p.kblocks - 4) {
            const int row0 = rt * 128 + wg * 64 + (warp & 3) * 16 + (lane >> 2);
            g0 = __ldg(p.gate + row0); g1 = __ldg(p.gate + row0 + 8);
#pragma unroll
            for (int j = 0; j < BN / 8; j++) {
              const int col = ct * BN + j * 8 + (lane & 3) * 2;
              bpre[j][0] = __ldg(reinterpret_cast<const uint32_t*>(p.bmix + (size_t)row0 * DM + col));
              bpre[j][1] = __ldg(reinterpret_cast<const uint32_t*>(p.bmix + (size_t)(row0 + 8) * DM + col));
            }
          }
        }
        mbar_wait(bar_full + 8 * st, ph);
        const uint32_t sa = sb + st * C::STAGE_BYTES + wg * 8192, sbb = sb + st * C::STAGE_BYTES + C::A_BYTES;
        wgmma_fence();
#pragma unroll
        for (int k = 0; k < 4; k++) {
          const uint64_t da = make_desc(sa + k * 32, 16, 1024);
          const uint64_t db = make_desc(sbb + k * 2048, 8192, 1024);
          if constexpr (BN == 256) wgmma_m64n256k16_tb1(acc, da, db, (kb | k) != 0);
          else wgmma_m64n128k16_tb1(acc, da, db, (kb | k) != 0);
        }
        wgmma_commit();
        if (prev >= 0) { wgmma_wait<1>(); RELEASE(prev); }
        prev = st;
        if (++st == C::STAGES) { st = 0; ph ^= 1; }
      }
      wgmma_wait<0>();
      RELEASE(prev);
      const int w4 = warp & 3;
      if constexpr (EPI == 0) {
        const uint32_t stg = sb + C::OFF_EPI + wg * 16384;
        const int r = w4 * 16 + (lane & 7) + ((lane >> 3) & 1) * 8;
#pragma unroll
        for (int sub = 0; sub < BN / 64; sub++) {
          const int slot = sub & 1;
          mbar_wait(bar_sempty + 8 * (2 * wg + slot), (((sub >> 1) & 1) ^ 1) ^ (BN == 128 ? sph : 0));
#pragma unroll
          for (int jj = 0; jj < 4; jj++) {
            const int j = sub * 4 + jj;
            const int chunk = 2 * jj + (lane >> 4);
            stsm_x4(stg + slot * 8192 + r * 128 + ((chunk ^ (r & 7)) << 4),
                    pack_bf16(acc[8 * j + 0], acc[8 * j + 1]), pack_bf16(acc[8 * j + 2], acc[8 * j + 3]),
                    pack_bf16(acc[8 * j + 4], acc[8 * j + 5]), pack_bf16(acc[8 * j + 6], acc[8 * j + 7]));
          }
          fence_proxy_async_smem();
          mbar_arrive(bar_sfull + 8 * (2 * wg + slot));
        }
        sph ^= 1;
      } else {
        const int row0 = rt * 128 + wg * 64 + w4 * 16 + (lane >> 2);
        const float h0 = round_bf16(1.0f - g0), h1 = round_bf16(1.0f - g1);
#pragma unroll
        for (int j = 0; j < BN / 8; j++) {
          const int col = ct * BN + j * 8 + (lane & 3) * 2;
          const uint32_t b0 = bpre[j][0], b1 = bpre[j][1];
          const float a00 = round_bf16(acc[4 * j + 0]), a01 = round_bf16(acc[4 * j + 1]), a10 = round_bf16(acc[4 * j + 2]), a11 = round_bf16(acc[4 * j + 3]);
          const float o00 = round_bf16(g0 * a00) + round_bf16(h0 * bf16_lo(b0)), o01 = round_bf16(g0 * a01) + round_bf16(h0 * bf16_hi(b0));
          const float o10 = round_bf16(g1 * a10) + round_bf16(h1 * bf16_lo(b1)), o11 = round_bf16(g1 * a11) + round_bf16(h1 * bf16_hi(b1));
          *reinterpret_cast<uint32_t*>(p.out + (size_t)row0 * DM + col) = pack_bf16(o00, o01);
          *reinterpret_cast<uint32_t*>(p.out + (size_t)(row0 + 8) * DM + col) = pack_bf16(o10, o11);
        }
      }
    }
    TS_END(EPI == 0 ? 1 : 5 + p.kid);
    if constexpr (EPI == 1) {
      if (p.bump_epoch && blockIdx.x == 0 && tid == 0) atomicAdd(p.epoch, 1u);
    }
  }
  if (CM > 1) { __syncthreads(); cluster_sync_all(); }
}
namespace attn {
constexpr int OFF_Q = 0, OFF_K = 16384, OFF_V = 32768, OFF_KM = 49152, OFF_VM = 53248, OFF_BAR = 57344, SMEM = OFF_BAR + 64;
}
struct AttnParams {
  int rt_begin;
  const unsigned* m_flags;
  const unsigned* epoch;
  int kid;
  unsigned* o_flags;
};
DEVINL unsigned ld_acquire(const unsigned* p) { unsigned v; asm volatile("ld.acquire.gpu.global.u32 %0, [%1];" : "=r"(v) : "l"(p) : "memory"); return v; }

__global__ void __launch_bounds__(128) attn_kernel(const __grid_constant__ CUtensorMap tmQKV, const __grid_constant__ CUtensorMap tmKM,
                                                   const __grid_constant__ CUtensorMap tmVM, const __grid_constant__ CUtensorMap tmO, AttnParams p) {
  using namespace attn;
  extern __shared__ __align__(1024) uint8_t smem_raw[];
  const uint32_t sb = smem_u32(smem_raw);
  const int tid = threadIdx.x, warp = tid >> 5, lane = tid & 31;
  const int head = blockIdx.x & 31, rt = p.rt_begin + (blockIdx.x >> 5);
  const uint32_t bar0 = sb + OFF_BAR, bar1 = bar0 + 8;
  TS_BEGIN(4 + p.kid);
  if (tid == 0) {
    mbar_init(bar0, 1); mbar_init(bar1, 1);
    asm volatile("fence.mbarrier_init.release.cluster;" ::: "memory");
    fence_proxy_async();
    mbar_expect_tx(bar0, 49152);
#pragma unroll
    for (int m = 0; m < 3; m++)
#pragma unroll
      for (int h = 0; h < 2; h++) tma_load_2d(sb + m * 16384 + h * 8192, &tmQKV, m * HD + head * DH + h * 64, rt * 64, bar0);
  }
  __syncthreads();
  if (warp == 1) {
    const unsigned tag = *(volatile const unsigned*)p.epoch + 1;
    if (lane < 4) {
      const unsigned* f = p.m_flags + (rt * 2 + (lane >> 1)) * 64 + head * 2 + (lane & 1);
      uint32_t n = 0;
      while (ld_acquire(f) != tag) { __nanosleep(100); if (++n > (1u << 24)) __trap(); }
    }
    __syncwarp();
    if (lane == 0) {
      fence_proxy_async();
      mbar_expect_tx(bar1, 8192);
#pragma unroll
      for (int h = 0; h < 2; h++) {
        tma_load_2d(sb + OFF_KM + h * 2048, &tmKM, head * DH + h * 64, rt * 16, bar1);
        tma_load_2d(sb + OFF_VM + h * 2048, &tmVM, head * DH + h * 64, rt * 16, bar1);
      }
    }
    __syncwarp();
  }
  const int sg = warp >> 1, hf = warp & 1;
  const int qrow = sg * 32 + hf * 16;
  mbar_wait(bar0, 0);
  float s[5][4];
#pragma unroll
  for (int j = 0; j < 5; j++) { s[j][0] = s[j][1] = s[j][2] = s[j][3] = 0.f; }
  const int ar = qrow + (lane & 7) + ((lane >> 3) & 1) * 8;
  uint32_t qf[8][4];
#pragma unroll
  for (int ks = 0; ks < 8; ks++) {
    const int chunk = (2 * ks + (lane >> 4)) & 7;
    ldsm_x4(sb + OFF_Q + (ks >> 2) * 8192 + ar * 128 + ((chunk ^ (ar & 7)) << 4), qf[ks][0], qf[ks][1], qf[ks][2], qf[ks][3]);
  }
  const int nx = hf ? 4 : 2;
#pragma unroll
  for (int j = 0; j < 4; j++) {
    if (j < nx) {
      const int kr = sg * 32 + j * 8 + (lane & 7);
#pragma unroll
      for (int kp = 0; kp < 4; kp++) {
        uint32_t b0, b1, b2, b3;
        const int chunk = (4 * kp + (lane >> 3)) & 7;
        ldsm_x4(sb + OFF_K + (kp >> 1) * 8192 + kr * 128 + ((chunk ^ (kr & 7)) << 4), b0, b1, b2, b3);
        mma16816(s[j], qf[2 * kp][0], qf[2 * kp][1], qf[2 * kp][2], qf[2 * kp][3], b0, b1);
        mma16816(s[j], qf[2 * kp + 1][0], qf[2 * kp + 1][1], qf[2 * kp + 1][2], qf[2 * kp + 1][3], b2, b3);
      }
    }
  }
  mbar_wait(bar1, 0);
  {
    const int kr = sg * 8 + (lane & 7);
#pragma unroll
    for (int kp = 0; kp < 4; kp++) {
      uint32_t b0, b1, b2, b3;
      const int chunk = (4 * kp + (lane >> 3)) & 7;
      ldsm_x4(sb + OFF_KM + (kp >> 1) * 2048 + kr * 128 + ((chunk ^ (kr & 7)) << 4), b0, b1, b2, b3);
      mma16816(s[4], qf[2 * kp][0], qf[2 * kp][1], qf[2 * kp][2], qf[2 * kp][3], b0, b1);
      mma16816(s[4], qf[2 * kp + 1][0], qf[2 * kp + 1][1], qf[2 * kp + 1][2], qf[2 * kp + 1][3], b2, b3);
    }
  }
  const int q0 = hf * 16 + (lane >> 2), q1 = q0 + 8;
  float m0 = fmaxf(s[4][0], s[4][1]), m1 = fmaxf(s[4][2], s[4][3]);
#pragma unroll
  for (int j = 0; j < 4; j++) {
    const int k0 = j * 8 + (lane & 3) * 2;
    if (k0 > q0) s[j][0] = -INFINITY;
    if (k0 + 1 > q0) s[j][1] = -INFINITY;
    if (k0 > q1) s[j][2] = -INFINITY;
    if (k0 + 1 > q1) s[j][3] = -INFINITY;
    m0 = fmaxf(m0, fmaxf(s[j][0], s[j][1])); m1 = fmaxf(m1, fmaxf(s[j][2], s[j][3]));
  }
  m0 = fmaxf(m0, __shfl_xor_sync(0xffffffffu, m0, 1)); m0 = fmaxf(m0, __shfl_xor_sync(0xffffffffu, m0, 2));
  m1 = fmaxf(m1, __shfl_xor_sync(0xffffffffu, m1, 1)); m1 = fmaxf(m1, __shfl_xor_sync(0xffffffffu, m1, 2));
  const float sc = 0.08838834764831845f * 1.4426950408889634f;
  uint32_t pa[5][2];
  float l0 = 0.f, l1 = 0.f;
#pragma unroll
  for (int j = 0; j < 5; j++) {
    pa[j][0] = pack_bf16(ex2((s[j][0] - m0) * sc), ex2((s[j][1] - m0) * sc));
    pa[j][1] = pack_bf16(ex2((s[j][2] - m1) * sc), ex2((s[j][3] - m1) * sc));
    l0 += bf16_lo(pa[j][0]) + bf16_hi(pa[j][0]); l1 += bf16_lo(pa[j][1]) + bf16_hi(pa[j][1]);
  }
  l0 += __shfl_xor_sync(0xffffffffu, l0, 1); l0 += __shfl_xor_sync(0xffffffffu, l0, 2);
  l1 += __shfl_xor_sync(0xffffffffu, l1, 1); l1 += __shfl_xor_sync(0xffffffffu, l1, 2);
  const float i0 = 1.0f / l0, i1 = 1.0f / l1;
  __syncwarp();
  const int orow = qrow + (lane & 7) + ((lane >> 3) & 1) * 8;
#pragma unroll
  for (int np = 0; np < 8; np++) {
    float o0[4] = {0.f, 0.f, 0.f, 0.f}, o1[4] = {0.f, 0.f, 0.f, 0.f};
    const int hh = np >> 2, cb = (np & 3) * 2;
    {
      const int vr = sg * 32 + (lane & 15), ch = cb + (lane >> 4);
      uint32_t b0, b1, b2, b3;
      ldsm_x4_t(sb + OFF_V + hh * 8192 + vr * 128 + ((ch ^ (vr & 7)) << 4), b0, b1, b2, b3);
      mma16816(o0, pa[0][0], pa[0][1], pa[1][0], pa[1][1], b0, b1);
      mma16816(o1, pa[0][0], pa[0][1], pa[1][0], pa[1][1], b2, b3);
      if (hf) {
        const int vr2 = vr + 16;
        ldsm_x4_t(sb + OFF_V + hh * 8192 + vr2 * 128 + ((ch ^ (vr2 & 7)) << 4), b0, b1, b2, b3);
        mma16816(o0, pa[2][0], pa[2][1], pa[3][0], pa[3][1], b0, b1);
        mma16816(o1, pa[2][0], pa[2][1], pa[3][0], pa[3][1], b2, b3);
      }
      const int mr = sg * 8 + (lane & 7), mc = cb + ((lane >> 3) & 1);
      uint32_t m0_, m1_;
      ldsm_x2_t(sb + OFF_VM + hh * 2048 + mr * 128 + ((mc ^ (mr & 7)) << 4), m0_, m1_);
      mma1688(o0, pa[4][0], pa[4][1], m0_);
      mma1688(o1, pa[4][0], pa[4][1], m1_);
    }
    const int chunk = cb + (lane >> 4);
    stsm_x4(sb + OFF_Q + hh * 8192 + orow * 128 + ((chunk ^ (orow & 7)) << 4),
            pack_bf16(o0[0] * i0, o0[1] * i0), pack_bf16(o0[2] * i1, o0[3] * i1),
            pack_bf16(o1[0] * i0, o1[1] * i0), pack_bf16(o1[2] * i1, o1[3] * i1));
  }
  fence_proxy_async_smem();
  __syncthreads();
  TS_END(4 + p.kid);
  if (tid == 0) {
    tma_store_2d(&tmO, sb + OFF_Q, head * DH, rt * 64);
    tma_store_2d(&tmO, sb + OFF_Q + 8192, head * DH + 64, rt * 64);
    bulk_commit();
    if (p.o_flags) { bulk_wait<0>(); __threadfence(); atomicAdd(p.o_flags + head, 1u); }
    else bulk_wait_read<0>();
  }
}

__global__ void gate_kernel(const unsigned* m_flags, const unsigned* epoch, int seg) {
  const unsigned tag = *(volatile const unsigned*)epoch + 1;
  const unsigned* f = m_flags + seg * 64 + threadIdx.x;
  uint32_t n = 0;
  while (ld_acquire(f) != tag) { __nanosleep(200); if (++n > (1u << 24)) __trap(); }
}
#define OUT_STAGES 4
namespace outp {
constexpr int STAGE_BYTES = 32768;
template <int KS> struct Cfg {
  static constexpr int STAGES = OUT_STAGES;
  static constexpr int OFF_RECV = STAGES * STAGE_BYTES;
  static constexpr int KB = 64 / KS;
  static constexpr int NT = 16 / KS;
  static constexpr int SLOT = 8 * NT * 512;
  static constexpr int OFF_BAR = OFF_RECV + (KS - 1) * SLOT;
  static constexpr int SMEM = OFF_BAR + 128;
};
}
struct OutParams {
  int rt_begin;
  const float* gate;
  const bf16* bmix;
  bf16* out;
  unsigned* epoch;
  int bump_epoch;
  int kid;
  const unsigned* o_flags;
};
template <int KS>
__global__ void __launch_bounds__(288, 1) out_kernel(const __grid_constant__ CUtensorMap tmA, const __grid_constant__ CUtensorMap tmB, OutParams p) {
  using namespace outp;
  using C = Cfg<KS>;
  constexpr int KB = C::KB, NT = C::NT, STAGES = C::STAGES, OFF_RECV = C::OFF_RECV;
  extern __shared__ __align__(1024) uint8_t smem_raw[];
  const uint32_t sb = smem_u32(smem_raw);
  const int tid = threadIdx.x, warp = tid >> 5, lane = tid & 31;
  uint32_t rank; asm volatile("mov.u32 %0, %%cluster_ctarank;" : "=r"(rank));
  const int tile = blockIdx.x / KS;
  const int rt = p.rt_begin + tile / 5, ct = tile % 5;
  const uint32_t bar_full = sb + C::OFF_BAR, bar_empty = bar_full + 8 * STAGES, bar_recv = bar_empty + 8 * STAGES;
  TS_BEGIN(5 + p.kid);
  if (tid == 0) {
    for (int i = 0; i < STAGES; i++) { mbar_init(bar_full + 8 * i, 1); mbar_init(bar_empty + 8 * i, 2); }
    mbar_init(bar_recv, 1);
    asm volatile("fence.mbarrier_init.release.cluster;" ::: "memory");
    fence_proxy_async();
    mbar_expect_tx(bar_recv, (KS - 1) * C::SLOT);
  }
  __syncthreads();
  cluster_sync_all();
  if (warp == 8) {
    if (lane == 0) {
      int st = 0; uint32_t ph = 0;
      const unsigned target = p.o_flags ? 2 * (*(volatile unsigned*)p.epoch + 1) : 0;
      for (int kb = 0; kb < KB; kb++) {
        const int kk = (rank * KB + kb) * 64;
        mbar_wait(bar_empty + 8 * st, ph ^ 1);
        const uint32_t sa = sb + st * STAGE_BYTES, sbb = sa + 16384;
        mbar_expect_tx(bar_full + 8 * st, STAGE_BYTES);
        tma_load_2d(sbb, &tmB, ct * 128, kk, bar_full + 8 * st);
        tma_load_2d(sbb + 8192, &tmB, ct * 128 + 64, kk, bar_full + 8 * st);
        if (p.o_flags && (kb & 1) == 0) { wait_counter(p.o_flags + (kk >> 7), target); fence_proxy_async(); }
        tma_load_2d(sa, &tmA, kk, rt * 128, bar_full + 8 * st);
        if (++st == STAGES) { st = 0; ph ^= 1; }
      }
    }
  } else {
    const int wg = warp >> 2, w4 = warp & 3;
    int st = 0; uint32_t ph = 0;
    float acc[64];
    int prev = -1;
    for (int kb = 0; kb < KB; kb++) {
      mbar_wait(bar_full + 8 * st, ph);
      const uint32_t sa = sb + st * STAGE_BYTES + wg * 8192, sbb = sb + st * STAGE_BYTES + 16384;
      wgmma_fence();
#pragma unroll
      for (int k = 0; k < 4; k++)
        wgmma_m64n128k16_tb1(acc, make_desc(sa + k * 32, 16, 1024), make_desc(sbb + k * 2048, 8192, 1024), (kb | k) != 0);
      wgmma_commit();
      if (prev >= 0) { wgmma_wait<1>(); if ((tid & 127) == 0) mbar_arrive(bar_empty + 8 * prev); }
      prev = st;
      if (++st == STAGES) { st = 0; ph ^= 1; }
    }
    wgmma_wait<0>();
    const int row0 = rt * 128 + wg * 64 + w4 * 16 + (lane >> 2);
    const int col0 = ct * 128 + rank * (NT * 8) + (lane & 3) * 2;
    uint32_t bv[NT][2];
#pragma unroll
    for (int j = 0; j < NT; j++) {
      bv[j][0] = __ldg(reinterpret_cast<const uint32_t*>(p.bmix + (size_t)row0 * DM + col0 + j * 8));
      bv[j][1] = __ldg(reinterpret_cast<const uint32_t*>(p.bmix + (size_t)(row0 + 8) * DM + col0 + j * 8));
    }
    const float g0 = __ldg(p.gate + row0), g1 = __ldg(p.gate + row0 + 8);
#pragma unroll
    for (int dr = 0; dr < KS; dr++) {
      if (dr != (int)rank) {
        const uint32_t slot = ((int)rank < dr) ? rank : rank - 1;
        const uint32_t da = mapa(sb + OFF_RECV + slot * C::SLOT + warp * (NT * 512) + lane * 16, dr), db = mapa(bar_recv, dr);
#pragma unroll
        for (int j = 0; j < NT; j++)
          st_async_v4(da + j * 512, __float_as_uint(acc[4 * NT * dr + 4 * j]), __float_as_uint(acc[4 * NT * dr + 4 * j + 1]),
                      __float_as_uint(acc[4 * NT * dr + 4 * j + 2]), __float_as_uint(acc[4 * NT * dr + 4 * j + 3]), db);
      }
    }
    float own[4 * NT];
#pragma unroll
    for (int dr = 0; dr < KS; dr++)
      if (dr == (int)rank) {
#pragma unroll
        for (int e = 0; e < 4 * NT; e++) own[e] = acc[4 * NT * dr + e];
      }
    mbar_wait(bar_recv, 0);
    const float h0 = round_bf16(1.0f - g0), h1 = round_bf16(1.0f - g1);
#pragma unroll
    for (int j = 0; j < NT; j++) {
      float a[4] = {own[4 * j], own[4 * j + 1], own[4 * j + 2], own[4 * j + 3]};
#pragma unroll
      for (int sidx = 0; sidx < KS - 1; sidx++) {
        const float4 v = lds128f(sb + OFF_RECV + sidx * C::SLOT + warp * (NT * 512) + j * 512 + lane * 16);
        a[0] += v.x; a[1] += v.y; a[2] += v.z; a[3] += v.w;
      }
      const uint32_t b0 = bv[j][0], b1 = bv[j][1];
      const float o00 = round_bf16(g0 * round_bf16(a[0])) + round_bf16(h0 * bf16_lo(b0)), o01 = round_bf16(g0 * round_bf16(a[1])) + round_bf16(h0 * bf16_hi(b0));
      const float o10 = round_bf16(g1 * round_bf16(a[2])) + round_bf16(h1 * bf16_lo(b1)), o11 = round_bf16(g1 * round_bf16(a[3])) + round_bf16(h1 * bf16_hi(b1));
      *reinterpret_cast<uint32_t*>(p.out + (size_t)row0 * DM + col0 + j * 8) = pack_bf16(o00, o01);
      *reinterpret_cast<uint32_t*>(p.out + (size_t)(row0 + 8) * DM + col0 + j * 8) = pack_bf16(o10, o11);
    }
  }
  __syncthreads();
  cluster_sync_all();
  TS_END(5 + p.kid);
  if (p.bump_epoch && tid == 0) {
    const unsigned n = atomicAdd(p.epoch + 1, 1u);
    if (n == gridDim.x - 1) { p.epoch[1] = 0; __threadfence(); atomicAdd(p.epoch, 1u); }
  }
}
struct SsmParams {
  const bf16 *A_re, *A_im, *B_re, *B_im, *C_re, *C_im, *log_dt, *Dskip, *x, *gate_w;
  bf16* kbf;
  bf16* xT;
  float* gate;
  bf16* bmix;
};
struct cplx { float re, im; };
DEVINL cplx cmul(cplx a, cplx b) { cplx r; r.re = fmaf(a.re, b.re, -a.im * b.im); r.im = fmaf(a.re, b.im, a.im * b.re); return r; }
DEVINL cplx csqr(cplx a) { cplx r; r.re = fmaf(a.re, a.re, -a.im * a.im); r.im = 2.0f * a.re * a.im; return r; }
DEVINL cplx cexp_scaled(float zr, float zi, float x) {
  const float mag = ex2(zr * x * 1.4426950408889634f);
  float t = (zi * x) * 0.15915494309189535f;
  t -= rintf(t);
  const float ang = t * 6.283185307179586f;
  cplx r; r.re = mag * __cosf(ang); r.im = mag * __sinf(ang); return r;
}
DEVINL uint32_t to_tf32(float x) { uint32_t r; asm("cvt.rna.tf32.f32 %0, %1;" : "=r"(r) : "f"(x)); return r; }
DEVINL void mma_tf32(float* c, const uint32_t* a, uint32_t b0, uint32_t b1) {
  asm volatile("mma.sync.aligned.m16n8k8.row.col.f32.tf32.tf32.f32 {%0,%1,%2,%3}, {%4,%5,%6,%7}, {%8,%9}, {%0,%1,%2,%3};"
    : "+f"(c[0]), "+f"(c[1]), "+f"(c[2]), "+f"(c[3]) : "r"(a[0]), "r"(a[1]), "r"(a[2]), "r"(a[3]), "r"(b0), "r"(b1));
}

__global__ void __launch_bounds__(256) ssm_gen_kernel(SsmParams p) {
  __shared__ __align__(16) float red[11][8][128];
  __shared__ float kd[648];
  const int tid = threadIdx.x, warp = tid >> 5, lane = tid & 31;
  if (blockIdx.x >= DM) {
    bf16 (*xs)[DM + 8] = reinterpret_cast<bf16 (*)[DM + 8]>(&red[0][0][0]);
    const int t0 = (blockIdx.x - DM) * 32;
    for (int i = tid; i < 32 * (DM / 8); i += 256) {
      const int r = i / (DM / 8), c = i % (DM / 8);
      *reinterpret_cast<uint4*>(&xs[r][c * 8]) = __ldg(reinterpret_cast<const uint4*>(p.x + (size_t)(t0 + r) * DM + c * 8));
    }
    __syncthreads();
    for (int r = warp; r < 32; r += 8) {
      float acc = 0.f;
      for (int c = lane * 2; c < DM; c += 64) {
        const uint32_t xv = *reinterpret_cast<const uint32_t*>(&xs[r][c]);
        const uint32_t wv = __ldg(reinterpret_cast<const uint32_t*>(p.gate_w + c));
        acc += round_bf16(bf16_lo(xv) * bf16_lo(wv)) + round_bf16(bf16_hi(xv) * bf16_hi(wv));
      }
#pragma unroll
      for (int o = 16; o > 0; o >>= 1) acc += __shfl_xor_sync(0xffffffffu, acc, o);
      if (lane == 0) {
        const float z = round_bf16(acc);
        p.gate[t0 + r] = round_bf16(1.0f / (1.0f + __expf(-z)));
      }
    }
    for (int i = tid; i < DM * 16; i += 256) {
      const int dd = i >> 4, r2 = (i & 15) * 2;
      __nv_bfloat162 v; v.x = xs[r2][dd]; v.y = xs[r2 + 1][dd];
      *reinterpret_cast<__nv_bfloat162*>(p.xT + (size_t)dd * 2176 + 128 + t0 + r2) = v;
    }
    if (t0 == 0) for (int i = tid; i < DM * 16; i += 256) *reinterpret_cast<uint4*>(p.xT + (size_t)(i >> 4) * 2176 + (i & 15) * 8) = make_uint4(0, 0, 0, 0);
    return;
  }
  const int d = blockIdx.x;
  const int g = lane >> 2, q = lane & 3;
  TS_BEGIN(2);
  const float dt = round_bf16(expf(__bfloat162float(p.log_dt[d])));
  float acc[8][4];
#pragma unroll
  for (int t = 0; t < 8; t++) { acc[t][0] = acc[t][1] = acc[t][2] = acc[t][3] = 0.f; }
  float pr[4][6];
#pragma unroll
  for (int ks = 0; ks < 4; ks++) {
    const int o = d * 128 + warp * 16 + ks * 4 + q;
    pr[ks][0] = __bfloat162float(p.A_re[o]); pr[ks][1] = __bfloat162float(p.A_im[o]); pr[ks][2] = __bfloat162float(p.B_re[o]);
    pr[ks][3] = __bfloat162float(p.B_im[o]); pr[ks][4] = __bfloat162float(p.C_re[o]); pr[ks][5] = __bfloat162float(p.C_im[o]);
  }
#pragma unroll
  for (int ks = 0; ks < 4; ks++) {
    const float zr = dt * pr[ks][0], zi = dt * pr[ks][1];
    cplx dB = {dt * pr[ks][2], dt * pr[ks][3]};
    cplx Cc = {pr[ks][4], pr[ks][5]};
    const cplx W = cmul(Cc, dB);
    cplx e[8], E[9];
    e[0] = cexp_scaled(zr, zi, (float)g);
    e[1] = csqr(e[0]); e[2] = csqr(e[1]); e[3] = csqr(e[2]);
    e[4] = cexp_scaled(zr, zi, (float)(16 * g));
    e[5] = csqr(e[4]); e[6] = csqr(e[5]); e[7] = csqr(e[6]);
    {
      const cplx mine = cexp_scaled(zr, zi, (float)(8 << g));
#pragma unroll
      for (int k = 0; k < 8; k++) { E[k].re = __shfl_sync(0xffffffffu, mine.re, k * 4 + q); E[k].im = __shfl_sync(0xffffffffu, mine.im, k * 4 + q); }
      E[8] = csqr(E[7]);
    }
    uint32_t A0[4], A1[4], A2[4];
    {
      const cplx x0 = cmul(W, e[4]);
      const cplx x1 = cmul(x0, E[4]);
      A0[0] = to_tf32(x0.re); A0[1] = to_tf32(x1.re); A0[2] = to_tf32(x0.im); A0[3] = to_tf32(x1.im);
      const cplx y0 = cmul(cmul(W, E[5]), e[5]);
      const cplx y1 = cmul(cmul(W, E[6]), e[6]);
      A1[0] = to_tf32(y0.re); A1[1] = to_tf32(y1.re); A1[2] = to_tf32(y0.im); A1[3] = to_tf32(y1.im);
      const cplx w0 = cmul(cmul(W, E[7]), e[7]);
      const cplx w1 = cmul(W, E[8]);
      A2[0] = to_tf32(w0.re); A2[1] = to_tf32(w1.re); A2[2] = to_tf32(w0.im); A2[3] = to_tf32(w1.im);
    }
#pragma unroll
    for (int r = 0; r < 4; r++) {
      const cplx f0 = e[r];
      const cplx f1 = cmul(f0, E[r]);
      const uint32_t* A = (r == 0) ? A0 : (r == 3) ? A2 : A1;
      mma_tf32(acc[2 * r], A, to_tf32(f0.re), to_tf32(-f0.im));
      mma_tf32(acc[2 * r + 1], A, to_tf32(f1.re), to_tf32(-f1.im));
    }
  }
#pragma unroll
  for (int t = 0; t < 8; t++) {
    red[warp][t][g * 8 + 2 * q] = acc[t][0]; red[warp][t][g * 8 + 2 * q + 1] = acc[t][1];
    red[warp][t][(g + 8) * 8 + 2 * q] = acc[t][2]; red[warp][t][(g + 8) * 8 + 2 * q + 1] = acc[t][3];
  }
  __syncthreads();
  for (int i = tid; i < 1024; i += 256) {
    const int t = i >> 7, row = (i >> 3) & 15, col = i & 7;
    float s = 0.f;
#pragma unroll
    for (int w = 0; w < 8; w++) s += red[w][t][row * 8 + col];
    const int r = t >> 1, b = (t & 1) * 8 + col;
    int idx = -1;
    if (r == 0) idx = 16 * row + b;
    else if (r == 1) { if (row < 8) idx = 256 + 16 * row + b; }
    else if (r == 2) { if (row >= 8) idx = 384 + 16 * (row - 8) + b; }
    else { if (row < 8) idx = 512 + 16 * row + b; else if (row == 8 && b == 0) idx = 640; }
    if (idx >= 0) kd[idx] = s;
  }
  __syncthreads();
  for (int j8 = tid; j8 < 520; j8 += 256) {
    const int which = j8 >= 260, j = (j8 - which * 260) * 8;
    uint32_t w[4];
#pragma unroll
    for (int e = 0; e < 8; e++) {
      const int l = 2047 - which - (j + e);
      float v = 0.f;
      if (l >= 0) {
        const int sh = (l < 256) ? 0 : (l < 512) ? 1 : (l < 1024) ? 2 : 3;
        const int m = sh ? ((l + ((1 << sh) >> 1) - 1 + ((l >> sh) & 1)) >> sh) : l;
        v = kd[m + 128 * sh];
      }
      const uint32_t h = (uint32_t)__bfloat16_as_ushort(__float2bfloat16_rn(v));
      if (e & 1) w[e >> 1] |= h << 16; else w[e >> 1] = h;
    }
    *reinterpret_cast<uint4*>(p.kbf + ((size_t)d * 2 + which) * 2080 + j) = make_uint4(w[0], w[1], w[2], w[3]);
  }
  TS_END(2);
}

namespace conv {
constexpr int CH = 4;
constexpr int U_LEN = 128 + 2048;
constexpr int R_LEN = 2048 + 32;
constexpr int OFF_U = 0;
constexpr int OFF_R0 = OFF_U + CH * U_LEN * 2;
constexpr int OFF_R1 = OFF_R0 + CH * R_LEN * 2;
constexpr int OFF_Y = OFF_R1 + CH * R_LEN * 2;
constexpr int OFF_BAR = OFF_Y + 2048 * CH * 2;
constexpr int SMEM = OFF_BAR + 16;
}
__global__ void __launch_bounds__(128) conv_kernel(SsmParams p) {
  using namespace conv;
  extern __shared__ __align__(1024) uint8_t smem_raw[];
  bf16* us = reinterpret_cast<bf16*>(smem_raw + OFF_U);
  bf16* r0 = reinterpret_cast<bf16*>(smem_raw + OFF_R0);
  bf16* r1 = reinterpret_cast<bf16*>(smem_raw + OFF_R1);
  bf16* ys = reinterpret_cast<bf16*>(smem_raw + OFF_Y);
  const int tid = threadIdx.x, warp = tid >> 5, lane = tid & 31;
  const int d0 = blockIdx.x * CH;
  TS_BEGIN(3);
  const uint32_t sb = smem_u32(smem_raw), bar = sb + OFF_BAR;
  if (tid == 0) {
    mbar_init(bar, 1);
    asm volatile("fence.mbarrier_init.release.cluster;" ::: "memory");
    fence_proxy_async();
    mbar_expect_tx(bar, CH * (U_LEN * 2 + 2 * R_LEN * 2));
    for (int c = 0; c < CH; c++) {
      bulk_load(sb + OFF_U + c * U_LEN * 2, p.xT + (size_t)(d0 + c) * U_LEN, U_LEN * 2, bar);
      bulk_load(sb + OFF_R0 + c * R_LEN * 2, p.kbf + ((size_t)(d0 + c) * 2) * R_LEN, R_LEN * 2, bar);
      bulk_load(sb + OFF_R1 + c * R_LEN * 2, p.kbf + ((size_t)(d0 + c) * 2 + 1) * R_LEN, R_LEN * 2, bar);
    }
  }
  __syncthreads();
  mbar_wait(bar, 0);
  const int g = lane >> 2, q = lane & 3;
  const uint32_t* up = reinterpret_cast<const uint32_t*>(us + warp * U_LEN + 128);
  const bf16* rp = (g & 1) ? (r0 + warp * R_LEN + 2047) : (r1 + warp * R_LEN + 2046);
  float acc[16][4];
#pragma unroll
  for (int j = 0; j < 16; j++) { acc[j][0] = acc[j][1] = acc[j][2] = acc[j][3] = 0.f; }
#pragma unroll 1
  for (int rho = 0; rho < 8; rho++) {
    uint32_t bfr[16][2];
#pragma unroll
    for (int j = 0; j < 16; j++) {
      const int w = (16 * (8 * j - rho + g) + 2 * q) >> 1;
      bfr[j][0] = up[w]; bfr[j][1] = up[w + 4];
    }
#pragma unroll
    for (int m = 0; m < 16; m++) {
      const int x = 16 * (8 * m + rho) + g - 2 * q;
      const uint32_t a0 = *reinterpret_cast<const uint32_t*>(rp - x);
      const uint32_t a1 = *reinterpret_cast<const uint32_t*>(rp - (x + 8));
      const uint32_t a2 = *reinterpret_cast<const uint32_t*>(rp - (x - 8));
#pragma unroll
      for (int j = m; j < 16; j++) mma16816(acc[j], a0, a1, a2, a0, bfr[j - m][0], bfr[j - m][1]);
    }
  }
  const float dsk = __bfloat162float(p.Dskip[d0 + warp]);
#pragma unroll
  for (int j = 0; j < 16; j++)
#pragma unroll
    for (int e = 0; e < 4; e++) {
      const int t = 16 * (8 * j + 2 * q + (e & 1)) + g + (e >> 1) * 8;
      const float u = __bfloat162float(us[warp * U_LEN + 128 + t]);
      ys[t * CH + warp] = __float2bfloat16_rn(round_bf16(acc[j][e]) + round_bf16(u * dsk));
    }
  __syncthreads();
  TS_END(3);
  for (int t = tid; t < SEQ; t += 128)
    *reinterpret_cast<uint2*>(p.bmix + (size_t)t * DM + d0) = *reinterpret_cast<const uint2*>(ys + t * CH);
}
typedef CUresult (*PFN_encodeTiled)(CUtensorMap*, CUtensorMapDataType, cuuint32_t, void*, const cuuint64_t*, const cuuint64_t*,
                                    const cuuint32_t*, const cuuint32_t*, CUtensorMapInterleave, CUtensorMapSwizzle,
                                    CUtensorMapL2promotion, CUtensorMapFloatOOBfill);
static PFN_encodeTiled get_encode() {
  static PFN_encodeTiled fn = nullptr;
  if (!fn) {
    void* p = nullptr; cudaDriverEntryPointQueryResult qr;
    cudaGetDriverEntryPoint("cuTensorMapEncodeTiled", &p, cudaEnableDefault, &qr);
    fn = (PFN_encodeTiled)p;
  }
  return fn;
}
static CUtensorMap make_tmap(const void* ptr, uint64_t rows, uint64_t cols, uint32_t br, uint32_t bc,
                             CUtensorMapSwizzle sw = CU_TENSOR_MAP_SWIZZLE_128B) {
  CUtensorMap m;
  cuuint64_t gd[2] = {cols, rows};
  cuuint64_t gs[1] = {cols * 2};
  cuuint32_t bd[2] = {bc, br};
  cuuint32_t es[2] = {1, 1};
  get_encode()(&m, CU_TENSOR_MAP_DATA_TYPE_BFLOAT16, 2, const_cast<void*>(ptr), gd, gs, bd, es, CU_TENSOR_MAP_INTERLEAVE_NONE, sw,
               CU_TENSOR_MAP_L2_PROMOTION_L2_256B, CU_TENSOR_MAP_FLOAT_OOB_FILL_NONE);
  return m;
}
__device__ bf16 g_qkv[(size_t)SEQ * 3 * HD];
__device__ bf16 g_o[(size_t)SEQ * HD];
__device__ bf16 g_km[NSEG * MTOK * HD];
__device__ bf16 g_vm[NSEG * MTOK * HD];
__device__ __align__(128) bf16 g_kbf[DM * 2 * 2080];
__device__ __align__(128) bf16 g_xT[DM * 2176];
__device__ bf16 g_bmix[SEQ * DM];
__device__ float g_gate[SEQ];
__device__ uint4 g_xbuf[2 * 4 * 16 * 80];
__device__ unsigned g_epoch[2];
__device__ unsigned g_oflags[32];
__device__ unsigned g_mflags[64 * 64];
__device__ unsigned g_kvflags[16 * 64];
__device__ long long g_prof[64 * 1024];

template <typename T> static T* sym_addr(const T& sym) { void* p = nullptr; cudaGetSymbolAddress(&p, sym); return (T*)p; }

struct HostState {
  bool init;
  const void* in_key[17]; void* out_key;
  CUtensorMap tmWq128, tmWk128, tmWv128, tmWoC, tmKV32;
  CUtensorMap tmX, tmWqB, tmWkB, tmWvB, tmQKVst;
  CUtensorMap tmQKV64, tmKM, tmVM, tmOst;
  CUtensorMap tmOA, tmWoB;
  cudaStream_t s2, s3, s4; cudaEvent_t evFork, evJoin, evQ, evQ0, evQ0done, evL, evSsm, evA[8], evO[8]; cudaStream_t so[8];
  int nsm;
};
static HostState H;

template <typename K, typename... Args>
static void launch_ex(K k, dim3 grid, dim3 block, int smem, cudaStream_t st, int cluster, cudaEvent_t launch_done, Args... args) {
  cudaLaunchConfig_t cfg = {};
  cfg.gridDim = grid; cfg.blockDim = block; cfg.dynamicSmemBytes = smem; cfg.stream = st;
  cudaLaunchAttribute at[2]; int n = 0;
  if (cluster > 1) { at[n].id = cudaLaunchAttributeClusterDimension; at[n].val.clusterDim.x = cluster; at[n].val.clusterDim.y = 1; at[n].val.clusterDim.z = 1; n++; }
  if (launch_done) { at[n].id = cudaLaunchAttributeLaunchCompletionEvent; at[n].val.launchCompletionEvent.event = launch_done; at[n].val.launchCompletionEvent.flags = 0; n++; }
  cfg.attrs = at; cfg.numAttrs = n;
  cudaLaunchKernelEx(&cfg, k, args...);
}

extern "C" void kernel_launch(void* const* d_in, const int* in_sizes, int n_in, void* d_out, int out_size);

#define CHUNKS {0, 4, 8, 11, 13, 14, 15, 16}
#define NSPLIT 3
#define LAST_KS 8
#define OUT_PRIO 1
#define SSM_PRIO 1
#define MODE 1

extern "C" void kernel_launch(void* const* d_in, const int* in_sizes, int n_in, void* d_out, int out_size) {
  const bf16 *x = (const bf16*)d_in[0], *mem0 = (const bf16*)d_in[1], *Wq = (const bf16*)d_in[2], *Wk = (const bf16*)d_in[3],
             *Wv = (const bf16*)d_in[4], *Wo = (const bf16*)d_in[5];
  bool rebuild = !H.init;
  for (int i = 0; i < 17 && !rebuild; i++) if (H.in_key[i] != d_in[i]) rebuild = true;
  if (!rebuild && H.out_key != d_out) rebuild = true;
  bf16* qkv = sym_addr(g_qkv[0]); bf16* o = sym_addr(g_o[0]); bf16* km = sym_addr(g_km[0]); bf16* vm = sym_addr(g_vm[0]);
  if (rebuild) {
    for (int i = 0; i < 17; i++) H.in_key[i] = d_in[i];
    H.out_key = d_out;
    H.tmWq128 = make_tmap(Wq, 640, 4096, 128, 64); H.tmWk128 = make_tmap(Wk, 640, 4096, 128, 64); H.tmWv128 = make_tmap(Wv, 640, 4096, 128, 64);
    H.tmWoC = make_tmap(Wo, 4096, 640, 128, 64); H.tmKV32 = make_tmap(qkv, 2048, 12288, 32, 64);
    H.tmX = make_tmap(x, 2048, 640, 128, 64);
    H.tmWqB = make_tmap(Wq, 640, 4096, 64, 64); H.tmWkB = make_tmap(Wk, 640, 4096, 64, 64); H.tmWvB = make_tmap(Wv, 640, 4096, 64, 64);
    H.tmQKVst = make_tmap(qkv, 2048, 12288, 64, 64); H.tmQKV64 = H.tmQKVst;
    H.tmKM = make_tmap(km, 512, 4096, 16, 64); H.tmVM = make_tmap(vm, 512, 4096, 16, 64);
    H.tmOst = make_tmap(o, 2048, 4096, 64, 64);
    H.tmOA = make_tmap(o, 2048, 4096, 128, 64); H.tmWoB = make_tmap(Wo, 4096, 640, 64, 64);
    if (!H.init) {
      cudaFuncSetAttribute(chain_kernel, cudaFuncAttributeMaxDynamicSharedMemorySize, chain::SMEM_BYTES);
      cudaFuncSetAttribute(chain_kernel, cudaFuncAttributeNonPortableClusterSizeAllowed, 1);
      cudaFuncSetAttribute(gemm_kernel<128, 1, 1>, cudaFuncAttributeMaxDynamicSharedMemorySize, gemm::Cfg<128>::SMEM);
      cudaFuncSetAttribute(gemm_kernel<256, 0, 2>, cudaFuncAttributeMaxDynamicSharedMemorySize, gemm::Cfg<256>::SMEM);
      cudaFuncSetAttribute(gemm_kernel<128, 0, 1>, cudaFuncAttributeMaxDynamicSharedMemorySize, gemm::Cfg<128>::SMEM);
      cudaEventCreateWithFlags(&H.evQ0, cudaEventDisableTiming); cudaEventCreateWithFlags(&H.evQ0done, cudaEventDisableTiming);
      cudaFuncSetAttribute(out_kernel<2>, cudaFuncAttributeMaxDynamicSharedMemorySize, outp::Cfg<2>::SMEM);
      cudaFuncSetAttribute(out_kernel<4>, cudaFuncAttributeMaxDynamicSharedMemorySize, outp::Cfg<4>::SMEM);
      cudaFuncSetAttribute(out_kernel<8>, cudaFuncAttributeMaxDynamicSharedMemorySize, outp::Cfg<8>::SMEM);
      cudaEventCreateWithFlags(&H.evL, cudaEventDisableTiming);
      cudaDeviceGetAttribute(&H.nsm, cudaDevAttrMultiProcessorCount, 0);
      cudaFuncSetAttribute(attn_kernel, cudaFuncAttributeMaxDynamicSharedMemorySize, attn::SMEM);
      cudaFuncSetAttribute(conv_kernel, cudaFuncAttributeMaxDynamicSharedMemorySize, conv::SMEM);
      cudaStreamCreateWithFlags(&H.s2, cudaStreamNonBlocking);
      int prio_lo = 0, prio_hi = 0; cudaDeviceGetStreamPriorityRange(&prio_lo, &prio_hi);
      cudaStreamCreateWithFlags(&H.s3, cudaStreamNonBlocking); cudaStreamCreateWithPriority(&H.s4, cudaStreamNonBlocking, SSM_PRIO ? prio_hi : prio_lo);
      cudaEventCreateWithFlags(&H.evQ, cudaEventDisableTiming); cudaEventCreateWithFlags(&H.evSsm, cudaEventDisableTiming);
      for (int i = 0; i < 8; i++) { cudaEventCreateWithFlags(&H.evA[i], cudaEventDisableTiming); cudaEventCreateWithFlags(&H.evO[i], cudaEventDisableTiming); cudaStreamCreateWithPriority(&H.so[i], cudaStreamNonBlocking, OUT_PRIO ? prio_hi : prio_lo); }
      cudaEventCreateWithFlags(&H.evFork, cudaEventDisableTiming);
      cudaEventCreateWithFlags(&H.evJoin, cudaEventDisableTiming);
    }
    H.init = true;
  }
  cudaStream_t s1 = cudaStreamPerThread;
  ChainParams cp;
  cp.Wq = Wq; cp.Wk = Wk; cp.Wv = Wv; cp.Wo = Wo;
  cp.mem0 = mem0; cp.km = km; cp.vm = vm; cp.xbuf = sym_addr(g_xbuf[0]); cp.epoch = sym_addr(g_epoch[0]); cp.kv_flags = sym_addr(g_kvflags[0]);
  cp.m_flags = sym_addr(g_mflags[0]); cp.prof = sym_addr(g_prof[0]);
  GemmParams g1 = {}; g1.tile_begin = 0; g1.tile_end = 352; g1.kblocks = 10; g1.flags = cp.kv_flags;
  SsmParams sp;
  sp.A_re = (const bf16*)d_in[8]; sp.A_im = (const bf16*)d_in[9]; sp.B_re = (const bf16*)d_in[10]; sp.B_im = (const bf16*)d_in[11];
  sp.C_re = (const bf16*)d_in[12]; sp.C_im = (const bf16*)d_in[13]; sp.log_dt = (const bf16*)d_in[14]; sp.Dskip = (const bf16*)d_in[15];
  sp.x = x; sp.gate_w = (const bf16*)d_in[16]; sp.kbf = sym_addr(g_kbf[0]); sp.xT = sym_addr(g_xT[0]); sp.gate = sym_addr(g_gate[0]); sp.bmix = sym_addr(g_bmix[0]);
  AttnParams ap; ap.o_flags = nullptr; ap.kid = 0; ap.rt_begin = 0; ap.m_flags = cp.m_flags; ap.epoch = cp.epoch;
  GemmParams g2 = {}; g2.tile_begin = 0; g2.tile_end = 80; g2.kblocks = 64; g2.gate = sp.gate; g2.bmix = sp.bmix; g2.out = (bf16*)d_out;
  g2.epoch = cp.epoch; g2.bump_epoch = 1;

  cudaStream_t s2 = H.s2, s4 = H.s4;
  launch_ex(chain_kernel, dim3(64), dim3(256), chain::SMEM_BYTES, s1, 16, H.evFork, H.tmWq128, H.tmWk128, H.tmWv128, H.tmWoC, H.tmKV32, cp);
  cudaStreamWaitEvent(H.s3, H.evFork, 0);
  GemmParams g0 = g1; g0.tile_begin = 0; g0.tile_end = 128;
  launch_ex(gemm_kernel<128, 0, 1>, dim3(64), dim3(320), gemm::Cfg<128>::SMEM, H.s3, 1, H.evQ0, H.tmX, H.tmWqB, H.tmWkB, H.tmWvB, H.tmQKVst, g0);
  cudaEventRecord(H.evQ0done, H.s3);
  cudaStreamWaitEvent(s2, H.evQ0, 0);
  launch_ex(gemm_kernel<256, 0, 2>, dim3((H.nsm - 64) & ~1), dim3(320), gemm::Cfg<256>::SMEM, s2, 2, H.evQ, H.tmX, H.tmWqB, H.tmWkB, H.tmWvB, H.tmQKVst, g1);
  cudaStreamWaitEvent(s2, H.evQ0done, 0);
  cudaStreamWaitEvent(s4, H.evQ, 0);
  launch_ex(ssm_gen_kernel, dim3(640 + 64), dim3(256), 0, s4, 1, nullptr, sp);
  launch_ex(conv_kernel, dim3(160), dim3(128), conv::SMEM, s4, 1, nullptr, sp);
  cudaEventRecord(H.evSsm, s4);
  {
    const int bounds[] = CHUNKS;
    const int nch = sizeof(bounds) / sizeof(int) - 1;
    for (int c = 0; c < nch; c++) {
      const int r0 = bounds[c], r1 = bounds[c + 1];
      const bool lastc = (c == nch - 1);
      ap.rt_begin = 2 * r0; ap.kid = 2 * c;
      if (!lastc) launch_ex(gate_kernel, dim3(1), dim3(64), 0, s2, 1, nullptr, (const unsigned*)cp.m_flags, (const unsigned*)cp.epoch, 4 * r1 - 1);
      ap.o_flags = lastc ? sym_addr(g_oflags[0]) : nullptr;
      launch_ex(attn_kernel, dim3(64 * (r1 - r0)), dim3(128), attn::SMEM, s2, 1, lastc ? H.evL : nullptr, H.tmQKV64, H.tmKM, H.tmVM, H.tmOst, ap);
      cudaStream_t so = H.so[c];
      if (lastc) {
        cudaStreamWaitEvent(so, H.evL, 0);
        cudaEventRecord(H.evA[c], s2);
        cudaStreamWaitEvent(s1, H.evA[c], 0);
      } else {
        cudaEventRecord(H.evA[c], s2);
        cudaStreamWaitEvent(so, H.evA[c], 0);
      }
      cudaStreamWaitEvent(so, H.evSsm, 0);
      if (c < nch - NSPLIT) {
        GemmParams gp = g2; gp.tile_begin = 5 * r0; gp.tile_end = 5 * r1; gp.bump_epoch = 0; gp.kid = 2 * c;
        launch_ex(gemm_kernel<128, 1, 1>, dim3(5 * (r1 - r0)), dim3(320), gemm::Cfg<128>::SMEM, so, 1, nullptr, H.tmOA, H.tmWoB, H.tmWoB, H.tmWoB, H.tmOst, gp);
      } else {
        OutParams op; op.rt_begin = r0; op.gate = sp.gate; op.bmix = sp.bmix; op.out = (bf16*)d_out; op.epoch = cp.epoch; op.bump_epoch = lastc; op.kid = 2 * c;
        op.o_flags = ap.o_flags;
        if (lastc && LAST_KS == 8) launch_ex(out_kernel<8>, dim3(5 * (r1 - r0) * 8), dim3(288), outp::Cfg<8>::SMEM, so, 8, nullptr, H.tmOA, H.tmWoB, op);
        else if (c < nch - 3) launch_ex(out_kernel<2>, dim3(5 * (r1 - r0) * 2), dim3(288), outp::Cfg<2>::SMEM, so, 2, nullptr, H.tmOA, H.tmWoB, op);
        else launch_ex(out_kernel<4>, dim3(5 * (r1 - r0) * 4), dim3(288), outp::Cfg<4>::SMEM, so, 4, nullptr, H.tmOA, H.tmWoB, op);
      }
      cudaEventRecord(H.evO[c], so);
      cudaStreamWaitEvent(s1, H.evO[c], 0);
    }
  }
}
```
